```python
import torch

def _softmax(x, axis=-1):
    return torch.softmax(x, dim=axis)

def _gelu(x):
    return torch.nn.functional.gelu(x, approximate='tanh')

def _silu(x):
    return torch.nn.functional.silu(x)

def _sigmoid(x):
    return torch.sigmoid(x)

def _layernorm(x, axis=-1, eps=1e-05):
    m = x.mean(dim=axis, keepdim=True)
    v = x.var(dim=axis, keepdim=True, unbiased=False)
    return (x - m) / torch.sqrt(v + eps)

def _scatter_add(tgt, idx, src, axis=0):
    return tgt.clone().index_add_(axis, idx, src)

def _segment_sum(src, seg, n):
    out = torch.zeros((n,) + src.shape[1:], dtype=src.dtype)
    return out.index_add_(0, seg, src)

def _pad(x, pw):
    flat = tuple((v for pair in reversed(pw) for v in pair))
    return torch.nn.functional.pad(x, flat)
kernel_name = 'adaLN_cond__sliding_block__moe_arch_mod__prompt'

def setup_inputs():

    _w = lambda a: (lambda t: t.to(torch.bfloat16) if t.is_floating_point() else t)(torch.as_tensor(a))

    def _A_setup():
        B, S, D = (1, 2048, 640)
        return {'x': _w((lambda *s: torch.randn(*s, dtype=torch.bfloat16) * 0.05)(B, S, D)), 'wqkv': _w((lambda *s: torch.randn(*s, dtype=torch.bfloat16) * 0.05)(D, 3 * D)), 'wo': _w((lambda *s: torch.randn(*s, dtype=torch.bfloat16) * 0.05)(D, D))}
    _A_in = _A_setup()

    def _B_setup():
        B, S, D, F, C = (1, 2048, 640, 1536, 2)
        return {'x': _w((lambda *s: torch.randn(*s, dtype=torch.bfloat16) * 0.05)(B, S, D)), 'w_r': _w((lambda *s: torch.randn(*s, dtype=torch.bfloat16) * 0.05)(D)), 'w_gate': _w((lambda *s: torch.randn(*s, dtype=torch.bfloat16) * 0.05)(D, F)), 'w_up': _w((lambda *s: torch.randn(*s, dtype=torch.bfloat16) * 0.05)(D, F)), 'w_down': _w((lambda *s: torch.randn(*s, dtype=torch.bfloat16) * 0.05)(F, D))}
    _B_in = _B_setup()
    return {'A_x': _A_in['x'], 'A_wqkv': _A_in['wqkv'], 'A_wo': _A_in['wo'], 'B_x': _B_in['x'], 'B_w_r': _B_in['w_r'], 'B_w_gate': _B_in['w_gate'], 'B_w_up': _B_in['w_up'], 'B_w_down': _B_in['w_down'], 'c': _w((lambda *s: torch.randn(*s, dtype=torch.bfloat16) * 0.1)(1, 640) * 8.0), 'w_mod': _w((lambda *s: torch.randn(*s, dtype=torch.bfloat16) * 0.1)(640, 6 * 640) * 640 ** (-0.5) * 8.0)}

def reference(A_x, A_wqkv, A_wo, B_x, B_w_r, B_w_gate, B_w_up, B_w_down, c, w_mod):

    def _A_ref(x, wqkv, wo):
        B, S, D = x.shape
        H = 32
        Dh = D // H
        W = 256
        qkv = (lambda x, *d: x.permute(*d))((x @ wqkv).reshape(B, S, 3, H, Dh), 2, 0, 3, 1, 4)
        q, k, v = (qkv[0], qkv[1], qkv[2])
        scores = torch.einsum('bhqd,bhkd->bhqk', q, k) * Dh ** (-0.5)
        idx = torch.arange(S)
        mask = (idx[:, None] - idx[None, :] >= 0) & (idx[:, None] - idx[None, :] < W)
        scores = torch.where(mask[None, None], scores, -1000000000.0)
        p = _softmax(scores, axis=-1)
        o = torch.einsum('bhqk,bhkd->bhqd', p, v)
        return (lambda x, *d: x.permute(*d))(o, 0, 2, 1, 3).reshape(B, S, D) @ wo

    def _B_ref(x, w_r, w_gate, w_up, w_down):
        B, S, D = x.shape
        C = 2
        r = x @ w_r
        idx = torch.argsort(-r, axis=-1)[:, :C]
        idx_e = (lambda x, n, axis: torch.repeat_interleave(x, n, dim=axis))(idx.reshape(B, C, 1), D, axis=2)
        x_sel = (lambda x, i, axis: torch.take_along_dim(x, i, dim=axis))(x, idx_e, axis=1)
        g = _silu(x_sel @ w_gate)
        u = x_sel @ w_up
        y = g * u @ w_down
        r_sel = _sigmoid((lambda x, i, axis: torch.take_along_dim(x, i, dim=axis))(r, idx, axis=1))
        y = y * r_sel.reshape(B, C, 1)
        b_off = (torch.arange(B) * S).reshape(B, 1)
        flat_idx = (idx + b_off).reshape(B * C)
        zero = (x * 0.0).reshape(B * S, D)
        upd = _scatter_add(zero, flat_idx, y.reshape(B * C, D), axis=0)
        return x + upd.reshape(B, S, D)
    x = A_x
    mod = (_silu(c) @ w_mod).reshape(c.shape[0], 6, 1, -1)
    sa, ca, ga, sb, cb, gb = (mod[:, 0].clone(), mod[:, 1].clone(), mod[:, 2].clone(), mod[:, 3].clone(), mod[:, 4].clone(), mod[:, 5].clone())
    h = _layernorm(x, axis=-1) * (1 + ca) + sa
    x = x + ga * _A_ref(h, A_wqkv, A_wo)
    h = _layernorm(x, axis=-1) * (1 + cb) + sb
    x = x + gb * _B_ref(h, B_w_r, B_w_gate, B_w_up, B_w_down)
    return x
```

```cpp
#include <cuda_runtime.h>
#include <cuda.h>
#include <cuda_bf16.h>
#include <stdint.h>

namespace {

constexpr int SEQ = 2048, DM = 640, FF = 1536;
constexpr int NCTA = 128, NTHR = 384;

constexpr int NSLOT = 4, CHUNK_B = 20480;
constexpr int OFF_RING = 0;
constexpr int KP = 5120, VP = 6144, KVH = KP + VP;
constexpr int KVR = 6 * KVH;
constexpr int OFF_KV = NSLOT * CHUNK_B;
constexpr int OFF_MISC = OFF_KV + 2 * KVR;
constexpr int OFF_X = OFF_MISC - 10 * 16384;
constexpr int OFF_MT = OFF_MISC;
constexpr int OFF_STG = OFF_MISC;
constexpr int OFF_TAB = OFF_MT + 8192;
constexpr int OFF_TABW = OFF_TAB + 1280;
constexpr int OFF_GBD = OFF_TABW + 1280;
constexpr int OFF_CONST = OFF_GBD + 64;
constexpr int OFF_RED = OFF_CONST + 16;
constexpr int OFF_RED2 = OFF_RED + 3072;
constexpr int OFF_CAND = OFF_RED2 + 128;
constexpr int OFF_BAR = OFF_CAND + 96;
constexpr int SMEM_BYTES = OFF_BAR + 64 * 8;
static_assert(OFF_BAR % 8 == 0 && OFF_X % 1024 == 0, "align");
static_assert(SMEM_BYTES <= 232448, "smem");
constexpr int WOSTEP_B = 5120;
constexpr int OFF_GU = OFF_KV;
constexpr int OFF_DN = OFF_KV + 40960;

enum {
    B_FULL = 0, B_EMPTY = 4, B_STG = 8  , B_X = 16  , B_WO = 26  , B_KREM = 34, B_VREM, B_KOWN, B_VOWN, B_HP0, B_ATT,
    B_MOD2, B_WODONE, B_GU, B_DN, B_TOP, B_KREP, B_XDONE, B_FFN, B_MSTG, B_MSTG2, B_MFREE, B_COUNT
};
static_assert(B_COUNT <= 64, "barriers");

#define VQ_AFTER 9
#define MOD_AT 8
constexpr uint32_t SPIN_MAX = 1u << 17;

struct Scratch {
    alignas(128) uint32_t g_epoch;
    alignas(128) uint4 g_mod1[640];
    alignas(128) uint2 g_mod[1280];
    alignas(128) uint2 g_msum[40];
    alignas(128) uint4 g_wq[8 * 15 * CHUNK_B / 16];
    alignas(128) uint32_t g_wflag[3 * 10 * 16];
    alignas(128) uint4 g_wo[4 * 40 * WOSTEP_B / 16];
    alignas(128) uint32_t g_woflag[2 * 96];
    alignas(128) uint4 g_gu[96 * 40960 / 16];
    alignas(128) uint4 g_dn[40 * 49152 / 16];
    alignas(128) uint4 g_kv[8 * 32 * 2 * KVH / 16];
    alignas(128) uint32_t g_kvflag[8 * 16 * 32];
    alignas(128) uint4 g_o[2 * 32 * 4 * 40 * 32];
    alignas(128) uint4 g_stat[SEQ * 8];
    alignas(128) uint4 g_cand[32 * 8];
    alignas(128) uint4 g_row[32 * 2 * 320];
    alignas(128) uint4 g_act[96 * 8];
};
__device__ Scratch g_scratch;
#define TSV(i, v) do { } while (0)
#define TW(acc, stmt) do { stmt; } while (0)
#define TS(i) do { } while (0)

__device__ __forceinline__ uint32_t smem_u32(const void* p) { return (uint32_t)__cvta_generic_to_shared(p); }
__device__ __forceinline__ void mbar_init(uint32_t bar, uint32_t cnt) { asm volatile("mbarrier.init.shared.b64 [%0], %1;" ::"r"(bar), "r"(cnt) : "memory"); }
__device__ __forceinline__ void mbar_arrive(uint32_t bar) { asm volatile("mbarrier.arrive.shared.b64 _, [%0];" ::"r"(bar) : "memory"); }
__device__ __forceinline__ void mbar_arrive_tx(uint32_t bar, uint32_t bytes) { asm volatile("mbarrier.arrive.expect_tx.shared.b64 _, [%0], %1;" ::"r"(bar), "r"(bytes) : "memory"); }
__device__ __forceinline__ bool mbar_try(uint32_t bar, uint32_t parity) {
    uint32_t done;
    asm volatile("{\n.reg .pred p;\nmbarrier.try_wait.parity.shared.b64 p, [%1], %2;\nselp.u32 %0, 1, 0, p;\n}" : "=r"(done) : "r"(bar), "r"(parity) : "memory");
    return done;
}
__device__ __forceinline__ void mbar_wait(uint32_t bar, uint32_t parity) {
    if (__builtin_expect(!mbar_try(bar, parity), 0)) {
#pragma unroll 1
        for (uint32_t it = 0; it < SPIN_MAX && !mbar_try(bar, parity); ++it) { }
    }
}
__device__ __forceinline__ void bulk_g2s(uint32_t dst, const void* src, uint32_t bytes, uint32_t bar) {
    asm volatile("cp.async.bulk.shared::cluster.global.mbarrier::complete_tx::bytes [%0], [%1], %2, [%3];" ::"r"(dst), "l"(src), "r"(bytes), "r"(bar) : "memory");
}
__device__ __forceinline__ void fence_async_smem() { asm volatile("fence.proxy.async.shared::cta;" ::: "memory"); }
__device__ __forceinline__ void fence_gpu() { asm volatile("fence.acq_rel.gpu;" ::: "memory"); }
__device__ __forceinline__ void bar_sync(int id, int n) { asm volatile("bar.sync %0, %1;" ::"r"(id), "r"(n) : "memory"); }
__device__ __forceinline__ void bar_arrive(int id, int n) { asm volatile("bar.arrive %0, %1;" ::"r"(id), "r"(n) : "memory"); }
#define WG_FENCE() asm volatile("wgmma.fence.sync.aligned;" ::: "memory")
#define WG_COMMIT() asm volatile("wgmma.commit_group.sync.aligned;" ::: "memory")
#define WG_WAIT(n) asm volatile("wgmma.wait_group.sync.aligned %0;" ::"n"(n) : "memory")
template <int N> __device__ __forceinline__ void pin(float (&d)[N]) {
#pragma unroll
    for (int i = 0; i < N; ++i) asm volatile("" : "+f"(d[i])::"memory");
}
__device__ __forceinline__ constexpr uint64_t mkdesc(uint32_t addr, uint32_t lbo, uint32_t sbo) {
    return (uint64_t)(((addr & 0x3FFFFu) >> 4) | ((lbo >> 4) << 16)) | ((uint64_t)(sbo >> 4) << 32);
}
__device__ __forceinline__ uint32_t pack_bf16(float lo, float hi) {
    uint32_t r; asm("cvt.rn.bf16x2.f32 %0, %1, %2;" : "=r"(r) : "f"(hi), "f"(lo)); return r;
}
__device__ __forceinline__ float bf_lo(uint32_t u) { return __uint_as_float(u << 16); }
__device__ __forceinline__ float bf_hi(uint32_t u) { return __uint_as_float(u & 0xffff0000u); }
__device__ __forceinline__ float rbf(float f) { return __bfloat162float(__float2bfloat16_rn(f)); }
__device__ __forceinline__ uint32_t hfma2_bf16(uint32_t a, uint32_t b, uint32_t c) {
    uint32_t r; asm("fma.rn.bf16x2 %0, %1, %2, %3;" : "=r"(r) : "r"(a), "r"(b), "r"(c)); return r;
}
__device__ __forceinline__ void hfma2_ip(uint32_t& a, uint32_t b, uint32_t c) { asm volatile("fma.rn.bf16x2 %0, %0, %1, %2;" : "+r"(a) : "r"(b), "r"(c)); }
template <int OFF> __device__ __forceinline__ void lds128(uint4& v, uint32_t base) {
    asm volatile("ld.shared.v4.u32 {%0,%1,%2,%3}, [%4+%5];" : "=r"(v.x), "=r"(v.y), "=r"(v.z), "=r"(v.w) : "r"(base), "n"(OFF) : "memory");
}
__device__ __forceinline__ float ex2(float x) { float r; asm("ex2.approx.ftz.f32 %0, %1;" : "=f"(r) : "f"(x)); return r; }
__device__ __forceinline__ uint4 ldg_nc(const void* p) {
    uint4 v; asm volatile("ld.global.nc.L1::no_allocate.v4.u32 {%0,%1,%2,%3}, [%4];" : "=r"(v.x), "=r"(v.y), "=r"(v.z), "=r"(v.w) : "l"(p)); return v;
}
__device__ __forceinline__ uint4 ldg_nc256(const void* p) {
    uint4 v; asm volatile("ld.global.nc.L1::no_allocate.L2::256B.v4.u32 {%0,%1,%2,%3}, [%4];" : "=r"(v.x), "=r"(v.y), "=r"(v.z), "=r"(v.w) : "l"(p)); return v;
}
__device__ __forceinline__ uint2 ld_ll8(const void* p) {
    uint64_t v; asm volatile("ld.relaxed.gpu.global.b64 %0, [%1];" : "=l"(v) : "l"(p) : "memory");
    return make_uint2((uint32_t)v, (uint32_t)(v >> 32));
}
__device__ __forceinline__ uint4 ld_ll16(const void* p) {
    uint64_t a, b; asm volatile("ld.relaxed.gpu.global.v2.b64 {%0,%1}, [%2];" : "=l"(a), "=l"(b) : "l"(p) : "memory");
    return make_uint4((uint32_t)a, (uint32_t)(a >> 32), (uint32_t)b, (uint32_t)(b >> 32));
}
__device__ __forceinline__ void st_ll8(void* p, uint32_t d, uint32_t ep) {
    asm volatile("st.relaxed.gpu.global.b64 [%0], %1;" ::"l"(p), "l"((uint64_t)d | ((uint64_t)ep << 32)) : "memory");
}
__device__ __forceinline__ void st_ll16(void* p, uint32_t d0, uint32_t d1, uint32_t ep) {
    asm volatile("st.relaxed.gpu.global.v2.b64 [%0], {%1,%2};" ::"l"(p), "l"((uint64_t)d0 | ((uint64_t)ep << 32)), "l"((uint64_t)d1 | ((uint64_t)ep << 32)) : "memory");
}
__device__ __forceinline__ uint4 ld_b128(const void* p) {
    uint4 v;
    asm volatile("{\n.reg .b128 r;\nld.relaxed.gpu.global.b128 r, [%4];\nmov.b128 {%0,%1,%2,%3}, r;\n}" : "=r"(v.x), "=r"(v.y), "=r"(v.z), "=r"(v.w) : "l"(p) : "memory");
    return v;
}
__device__ __forceinline__ void st_b128(void* p, uint32_t a, uint32_t b, uint32_t c, uint32_t d) {
    asm volatile("{\n.reg .b128 r;\nmov.b128 r, {%1,%2,%3,%4};\nst.relaxed.gpu.global.b128 [%0], r;\n}" ::"l"(p), "r"(a), "r"(b), "r"(c), "r"(d) : "memory");
}
__device__ __forceinline__ void st_flag(void* p, uint32_t ep) { asm volatile("st.relaxed.gpu.global.u32 [%0], %1;" ::"l"(p), "r"(ep) : "memory"); }
__device__ __forceinline__ void stmatrix4(uint32_t addr, uint32_t r0, uint32_t r1, uint32_t r2, uint32_t r3) {
    asm volatile("stmatrix.sync.aligned.m8n8.x4.shared.b16 [%0], {%1,%2,%3,%4};" ::"r"(addr), "r"(r0), "r"(r1), "r"(r2), "r"(r3) : "memory");
}
__device__ __forceinline__ void ldmatrix4_t(uint32_t (&r)[4], uint32_t addr) {
    asm volatile("ldmatrix.sync.aligned.m8n8.x4.trans.shared.b16 {%0,%1,%2,%3}, [%4];" : "=r"(r[0]), "=r"(r[1]), "=r"(r[2]), "=r"(r[3]) : "r"(addr) : "memory");
}
__device__ __forceinline__ void mma16816(float (&c)[4], const uint32_t (&a)[4], uint32_t b0, uint32_t b1) {
    asm volatile("mma.sync.aligned.m16n8k16.row.col.f32.bf16.bf16.f32 {%0,%1,%2,%3}, {%4,%5,%6,%7}, {%8,%9}, {%0,%1,%2,%3};"
                 : "+f"(c[0]), "+f"(c[1]), "+f"(c[2]), "+f"(c[3]) : "r"(a[0]), "r"(a[1]), "r"(a[2]), "r"(a[3]), "r"(b0), "r"(b1));
}
__device__ __forceinline__ void mma1688(float (&c)[4], uint32_t a0, uint32_t a1, uint32_t b0) {
    asm volatile("mma.sync.aligned.m16n8k8.row.col.f32.bf16.bf16.f32 {%0,%1,%2,%3}, {%4,%5}, {%6}, {%0,%1,%2,%3};"
                 : "+f"(c[0]), "+f"(c[1]), "+f"(c[2]), "+f"(c[3]) : "r"(a0), "r"(a1), "r"(b0));
}
__device__ __forceinline__ float rcp(float x) { float r; asm("rcp.approx.ftz.f32 %0, %1;" : "=f"(r) : "f"(x)); return r; }
__device__ __forceinline__ float sigmoidf_(float x) { return rcp(1.0f + ex2(x * -1.4426950408889634f)); }
__device__ __forceinline__ uint32_t hmul2_bf16(uint32_t a, uint32_t b) { uint32_t r; asm("mul.rn.bf16x2 %0, %1, %2;" : "=r"(r) : "r"(a), "r"(b)); return r; }
__device__ __forceinline__ uint32_t hadd2_bf16(uint32_t a, uint32_t b) { uint32_t r; asm("add.rn.bf16x2 %0, %1, %2;" : "=r"(r) : "r"(a), "r"(b)); return r; }
struct LnCoef { uint32_t rh, rl, nm; };
__device__ __forceinline__ LnCoef ln_coef(float mean, float rstd) {
    LnCoef c;
    c.rh = pack_bf16(rstd, rstd);
    const float l = rstd - bf_lo(c.rh), n = -mean * rstd;
    c.rl = pack_bf16(l, l);
    c.nm = pack_bf16(n, n);
    return c;
}
__device__ __forceinline__ uint32_t ln_apply(uint32_t x, const LnCoef& c) { return hfma2_bf16(x, c.rh, hfma2_bf16(x, c.rl, c.nm)); }

__device__ __forceinline__ void bulk_s2g(void* dst, uint32_t src, uint32_t bytes) {
    asm volatile("cp.async.bulk.global.shared::cta.bulk_group [%0], [%1], %2;" ::"l"(dst), "r"(src), "r"(bytes) : "memory");
}
__device__ __forceinline__ void bulk_commit_wait() {
    asm volatile("cp.async.bulk.commit_group;\ncp.async.bulk.wait_group 0;" ::: "memory");
}
__device__ __forceinline__ void tma_2d(uint32_t dst, const void* map, int c0, int c1, uint32_t bar) {
    asm volatile("cp.async.bulk.tensor.2d.shared::cluster.global.mbarrier::complete_tx::bytes [%0], [%1, {%3,%4}], [%2];"
                 ::"r"(dst), "l"(map), "r"(bar), "r"(c0), "r"(c1) : "memory");
}
__device__ __forceinline__ void ldmatrix4(uint32_t& r0, uint32_t& r1, uint32_t& r2, uint32_t& r3, uint32_t addr) {
    asm volatile("ldmatrix.sync.aligned.m8n8.x4.shared.b16 {%0,%1,%2,%3}, [%4];" : "=r"(r0), "=r"(r1), "=r"(r2), "=r"(r3) : "r"(addr) : "memory");
}
__device__ __forceinline__ uint32_t ld_flag(const void* p) {
    uint32_t v; asm volatile("ld.relaxed.gpu.global.u32 %0, [%1];" : "=r"(v) : "l"(p) : "memory"); return v;
}
__device__ __forceinline__ void fma8(float (&acc)[8], float s, const uint4& v) {
    acc[0] += s * bf_lo(v.x); acc[1] += s * bf_hi(v.x); acc[2] += s * bf_lo(v.y); acc[3] += s * bf_hi(v.y);
    acc[4] += s * bf_lo(v.z); acc[5] += s * bf_hi(v.z); acc[6] += s * bf_lo(v.w); acc[7] += s * bf_hi(v.w);
}
__device__ __forceinline__ float treduce8(const float (&acc)[8], int lane) {
    const bool u1 = lane & 4, u2 = lane & 8, u3 = lane & 16;
    float b4[4], b2[2];
#pragma unroll
    for (int i = 0; i < 4; ++i) { const float snd = u1 ? acc[i] : acc[i + 4], kp = u1 ? acc[i + 4] : acc[i]; b4[i] = kp + __shfl_xor_sync(~0u, snd, 4); }
#pragma unroll
    for (int i = 0; i < 2; ++i) { const float snd = u2 ? b4[i] : b4[i + 2], kp = u2 ? b4[i + 2] : b4[i]; b2[i] = kp + __shfl_xor_sync(~0u, snd, 8); }
    const float snd = u3 ? b2[0] : b2[1], kp = u3 ? b2[1] : b2[0];
    return kp + __shfl_xor_sync(~0u, snd, 16);
}
__device__ __forceinline__ float silu_bf(__nv_bfloat16 c) { const float f = __bfloat162float(c); return rbf(f * sigmoidf_(f)); }

__device__ __forceinline__ void wgmma_n80_init(float (&d)[40], uint32_t a0, uint32_t a1, uint32_t a2, uint32_t a3, uint64_t db) {
    asm volatile("wgmma.mma_async.sync.aligned.m64n80k16.f32.bf16.bf16 "
                 "{%0, %1, %2, %3, %4, %5, %6, %7, %8, %9, %10, %11, %12, %13, %14, %15, "
                 "%16, %17, %18, %19, %20, %21, %22, %23, %24, %25, %26, %27, %28, %29, %30, %31, "
                 "%32, %33, %34, %35, %36, %37, %38, %39}, "
                 "{%40,%41,%42,%43}, %44, 0, 1, 1, 1;\n"
                 : "=f"(d[0]), "=f"(d[1]), "=f"(d[2]), "=f"(d[3]), "=f"(d[4]), "=f"(d[5]), "=f"(d[6]), "=f"(d[7]),
                   "=f"(d[8]), "=f"(d[9]), "=f"(d[10]), "=f"(d[11]), "=f"(d[12]), "=f"(d[13]), "=f"(d[14]), "=f"(d[15]),
                   "=f"(d[16]), "=f"(d[17]), "=f"(d[18]), "=f"(d[19]), "=f"(d[20]), "=f"(d[21]), "=f"(d[22]), "=f"(d[23]),
                   "=f"(d[24]), "=f"(d[25]), "=f"(d[26]), "=f"(d[27]), "=f"(d[28]), "=f"(d[29]), "=f"(d[30]), "=f"(d[31]),
                   "=f"(d[32]), "=f"(d[33]), "=f"(d[34]), "=f"(d[35]), "=f"(d[36]), "=f"(d[37]), "=f"(d[38]), "=f"(d[39])
                 : "r"(a0), "r"(a1), "r"(a2), "r"(a3), "l"(db));
}
__device__ __forceinline__ void wgmma_n80(float (&d)[40], uint32_t a0, uint32_t a1, uint32_t a2, uint32_t a3, uint64_t db) {
    asm volatile("wgmma.mma_async.sync.aligned.m64n80k16.f32.bf16.bf16 "
                 "{%0, %1, %2, %3, %4, %5, %6, %7, %8, %9, %10, %11, %12, %13, %14, %15, "
                 "%16, %17, %18, %19, %20, %21, %22, %23, %24, %25, %26, %27, %28, %29, %30, %31, "
                 "%32, %33, %34, %35, %36, %37, %38, %39}, "
                 "{%40,%41,%42,%43}, %44, 1, 1, 1, 1;\n"
                 : "+f"(d[0]), "+f"(d[1]), "+f"(d[2]), "+f"(d[3]), "+f"(d[4]), "+f"(d[5]), "+f"(d[6]), "+f"(d[7]),
                   "+f"(d[8]), "+f"(d[9]), "+f"(d[10]), "+f"(d[11]), "+f"(d[12]), "+f"(d[13]), "+f"(d[14]), "+f"(d[15]),
                   "+f"(d[16]), "+f"(d[17]), "+f"(d[18]), "+f"(d[19]), "+f"(d[20]), "+f"(d[21]), "+f"(d[22]), "+f"(d[23]),
                   "+f"(d[24]), "+f"(d[25]), "+f"(d[26]), "+f"(d[27]), "+f"(d[28]), "+f"(d[29]), "+f"(d[30]), "+f"(d[31]),
                   "+f"(d[32]), "+f"(d[33]), "+f"(d[34]), "+f"(d[35]), "+f"(d[36]), "+f"(d[37]), "+f"(d[38]), "+f"(d[39])
                 : "r"(a0), "r"(a1), "r"(a2), "r"(a3), "l"(db));
}
__device__ __forceinline__ void wgmma_n64_init(float (&d)[32], uint32_t a0, uint32_t a1, uint32_t a2, uint32_t a3, uint64_t db) {
    asm volatile("wgmma.mma_async.sync.aligned.m64n64k16.f32.bf16.bf16 "
                 "{%0, %1, %2, %3, %4, %5, %6, %7, %8, %9, %10, %11, %12, %13, %14, %15, "
                 "%16, %17, %18, %19, %20, %21, %22, %23, %24, %25, %26, %27, %28, %29, %30, %31}, "
                 "{%32,%33,%34,%35}, %36, 0, 1, 1, 0;\n"
                 : "=f"(d[0]), "=f"(d[1]), "=f"(d[2]), "=f"(d[3]), "=f"(d[4]), "=f"(d[5]), "=f"(d[6]), "=f"(d[7]),
                   "=f"(d[8]), "=f"(d[9]), "=f"(d[10]), "=f"(d[11]), "=f"(d[12]), "=f"(d[13]), "=f"(d[14]), "=f"(d[15]),
                   "=f"(d[16]), "=f"(d[17]), "=f"(d[18]), "=f"(d[19]), "=f"(d[20]), "=f"(d[21]), "=f"(d[22]), "=f"(d[23]),
                   "=f"(d[24]), "=f"(d[25]), "=f"(d[26]), "=f"(d[27]), "=f"(d[28]), "=f"(d[29]), "=f"(d[30]), "=f"(d[31])
                 : "r"(a0), "r"(a1), "r"(a2), "r"(a3), "l"(db));
}
__device__ __forceinline__ void wgmma_n64(float (&d)[32], uint32_t a0, uint32_t a1, uint32_t a2, uint32_t a3, uint64_t db) {
    asm volatile("wgmma.mma_async.sync.aligned.m64n64k16.f32.bf16.bf16 "
                 "{%0, %1, %2, %3, %4, %5, %6, %7, %8, %9, %10, %11, %12, %13, %14, %15, "
                 "%16, %17, %18, %19, %20, %21, %22, %23, %24, %25, %26, %27, %28, %29, %30, %31}, "
                 "{%32,%33,%34,%35}, %36, 1, 1, 1, 0;\n"
                 : "+f"(d[0]), "+f"(d[1]), "+f"(d[2]), "+f"(d[3]), "+f"(d[4]), "+f"(d[5]), "+f"(d[6]), "+f"(d[7]),
                   "+f"(d[8]), "+f"(d[9]), "+f"(d[10]), "+f"(d[11]), "+f"(d[12]), "+f"(d[13]), "+f"(d[14]), "+f"(d[15]),
                   "+f"(d[16]), "+f"(d[17]), "+f"(d[18]), "+f"(d[19]), "+f"(d[20]), "+f"(d[21]), "+f"(d[22]), "+f"(d[23]),
                   "+f"(d[24]), "+f"(d[25]), "+f"(d[26]), "+f"(d[27]), "+f"(d[28]), "+f"(d[29]), "+f"(d[30]), "+f"(d[31])
                 : "r"(a0), "r"(a1), "r"(a2), "r"(a3), "l"(db));
}
__device__ __forceinline__ void wgmma_n24_init(float (&d)[12], uint32_t a0, uint32_t a1, uint32_t a2, uint32_t a3, uint64_t db) {
    asm volatile("wgmma.mma_async.sync.aligned.m64n24k16.f32.bf16.bf16 "
                 "{%0, %1, %2, %3, %4, %5, %6, %7, %8, %9, %10, %11}, "
                 "{%12,%13,%14,%15}, %16, 0, 1, 1, 1;\n"
                 : "=f"(d[0]), "=f"(d[1]), "=f"(d[2]), "=f"(d[3]), "=f"(d[4]), "=f"(d[5]), "=f"(d[6]), "=f"(d[7]),
                   "=f"(d[8]), "=f"(d[9]), "=f"(d[10]), "=f"(d[11])
                 : "r"(a0), "r"(a1), "r"(a2), "r"(a3), "l"(db));
}
__device__ __forceinline__ void wgmma_n24(float (&d)[12], uint32_t a0, uint32_t a1, uint32_t a2, uint32_t a3, uint64_t db) {
    asm volatile("wgmma.mma_async.sync.aligned.m64n24k16.f32.bf16.bf16 "
                 "{%0, %1, %2, %3, %4, %5, %6, %7, %8, %9, %10, %11}, "
                 "{%12,%13,%14,%15}, %16, 1, 1, 1, 1;\n"
                 : "+f"(d[0]), "+f"(d[1]), "+f"(d[2]), "+f"(d[3]), "+f"(d[4]), "+f"(d[5]), "+f"(d[6]), "+f"(d[7]),
                   "+f"(d[8]), "+f"(d[9]), "+f"(d[10]), "+f"(d[11])
                 : "r"(a0), "r"(a1), "r"(a2), "r"(a3), "l"(db));
}
__device__ __forceinline__ void wgmma_n160_init(float (&d)[80], uint32_t a0, uint32_t a1, uint32_t a2, uint32_t a3, uint64_t db) {
    asm volatile("wgmma.mma_async.sync.aligned.m64n160k16.f32.bf16.bf16 "
                 "{%0, %1, %2, %3, %4, %5, %6, %7, %8, %9, %10, %11, %12, %13, %14, %15, "
                 "%16, %17, %18, %19, %20, %21, %22, %23, %24, %25, %26, %27, %28, %29, %30, %31, "
                 "%32, %33, %34, %35, %36, %37, %38, %39, %40, %41, %42, %43, %44, %45, %46, %47, "
                 "%48, %49, %50, %51, %52, %53, %54, %55, %56, %57, %58, %59, %60, %61, %62, %63, "
                 "%64, %65, %66, %67, %68, %69, %70, %71, %72, %73, %74, %75, %76, %77, %78, %79}, "
                 "{%80,%81,%82,%83}, %84, 0, 1, 1, 1;\n"
                 : "=f"(d[0]), "=f"(d[1]), "=f"(d[2]), "=f"(d[3]), "=f"(d[4]), "=f"(d[5]), "=f"(d[6]), "=f"(d[7]),
                   "=f"(d[8]), "=f"(d[9]), "=f"(d[10]), "=f"(d[11]), "=f"(d[12]), "=f"(d[13]), "=f"(d[14]), "=f"(d[15]),
                   "=f"(d[16]), "=f"(d[17]), "=f"(d[18]), "=f"(d[19]), "=f"(d[20]), "=f"(d[21]), "=f"(d[22]), "=f"(d[23]),
                   "=f"(d[24]), "=f"(d[25]), "=f"(d[26]), "=f"(d[27]), "=f"(d[28]), "=f"(d[29]), "=f"(d[30]), "=f"(d[31]),
                   "=f"(d[32]), "=f"(d[33]), "=f"(d[34]), "=f"(d[35]), "=f"(d[36]), "=f"(d[37]), "=f"(d[38]), "=f"(d[39]),
                   "=f"(d[40]), "=f"(d[41]), "=f"(d[42]), "=f"(d[43]), "=f"(d[44]), "=f"(d[45]), "=f"(d[46]), "=f"(d[47]),
                   "=f"(d[48]), "=f"(d[49]), "=f"(d[50]), "=f"(d[51]), "=f"(d[52]), "=f"(d[53]), "=f"(d[54]), "=f"(d[55]),
                   "=f"(d[56]), "=f"(d[57]), "=f"(d[58]), "=f"(d[59]), "=f"(d[60]), "=f"(d[61]), "=f"(d[62]), "=f"(d[63]),
                   "=f"(d[64]), "=f"(d[65]), "=f"(d[66]), "=f"(d[67]), "=f"(d[68]), "=f"(d[69]), "=f"(d[70]), "=f"(d[71]),
                   "=f"(d[72]), "=f"(d[73]), "=f"(d[74]), "=f"(d[75]), "=f"(d[76]), "=f"(d[77]), "=f"(d[78]), "=f"(d[79])
                 : "r"(a0), "r"(a1), "r"(a2), "r"(a3), "l"(db));
}
__device__ __forceinline__ void wgmma_n160(float (&d)[80], uint32_t a0, uint32_t a1, uint32_t a2, uint32_t a3, uint64_t db) {
    asm volatile("wgmma.mma_async.sync.aligned.m64n160k16.f32.bf16.bf16 "
                 "{%0, %1, %2, %3, %4, %5, %6, %7, %8, %9, %10, %11, %12, %13, %14, %15, "
                 "%16, %17, %18, %19, %20, %21, %22, %23, %24, %25, %26, %27, %28, %29, %30, %31, "
                 "%32, %33, %34, %35, %36, %37, %38, %39, %40, %41, %42, %43, %44, %45, %46, %47, "
                 "%48, %49, %50, %51, %52, %53, %54, %55, %56, %57, %58, %59, %60, %61, %62, %63, "
                 "%64, %65, %66, %67, %68, %69, %70, %71, %72, %73, %74, %75, %76, %77, %78, %79}, "
                 "{%80,%81,%82,%83}, %84, 1, 1, 1, 1;\n"
                 : "+f"(d[0]), "+f"(d[1]), "+f"(d[2]), "+f"(d[3]), "+f"(d[4]), "+f"(d[5]), "+f"(d[6]), "+f"(d[7]),
                   "+f"(d[8]), "+f"(d[9]), "+f"(d[10]), "+f"(d[11]), "+f"(d[12]), "+f"(d[13]), "+f"(d[14]), "+f"(d[15]),
                   "+f"(d[16]), "+f"(d[17]), "+f"(d[18]), "+f"(d[19]), "+f"(d[20]), "+f"(d[21]), "+f"(d[22]), "+f"(d[23]),
                   "+f"(d[24]), "+f"(d[25]), "+f"(d[26]), "+f"(d[27]), "+f"(d[28]), "+f"(d[29]), "+f"(d[30]), "+f"(d[31]),
                   "+f"(d[32]), "+f"(d[33]), "+f"(d[34]), "+f"(d[35]), "+f"(d[36]), "+f"(d[37]), "+f"(d[38]), "+f"(d[39]),
                   "+f"(d[40]), "+f"(d[41]), "+f"(d[42]), "+f"(d[43]), "+f"(d[44]), "+f"(d[45]), "+f"(d[46]), "+f"(d[47]),
                   "+f"(d[48]), "+f"(d[49]), "+f"(d[50]), "+f"(d[51]), "+f"(d[52]), "+f"(d[53]), "+f"(d[54]), "+f"(d[55]),
                   "+f"(d[56]), "+f"(d[57]), "+f"(d[58]), "+f"(d[59]), "+f"(d[60]), "+f"(d[61]), "+f"(d[62]), "+f"(d[63]),
                   "+f"(d[64]), "+f"(d[65]), "+f"(d[66]), "+f"(d[67]), "+f"(d[68]), "+f"(d[69]), "+f"(d[70]), "+f"(d[71]),
                   "+f"(d[72]), "+f"(d[73]), "+f"(d[74]), "+f"(d[75]), "+f"(d[76]), "+f"(d[77]), "+f"(d[78]), "+f"(d[79])
                 : "r"(a0), "r"(a1), "r"(a2), "r"(a3), "l"(db));
}

struct Params {
    const __nv_bfloat16 *wmod, *c, *wqkv, *x;
    Scratch* s;
    const __nv_bfloat16 *wo, *wr;
    __nv_bfloat16* out;
};
struct Maps { CUtensorMap x, m, w[3]; };

__global__ void __launch_bounds__(NTHR, 1) fused_kernel(const __grid_constant__ Params P, const __grid_constant__ Maps M) {
    const int tid = threadIdx.x, bid = blockIdx.x, lane = tid & 31;
    const int rp_kc = (bid - 28) / 10, rp_line = (bid - 28) - rp_kc * 10;
    uint4 kr[2], mv[5];
    __nv_bfloat16 cv[5];
    if (tid < 256) {
        if (bid < 80) {
            const int r0 = (bid & 1) * 320 + (tid >> 2);
            const __nv_bfloat16* s = P.wmod + (size_t)r0 * 3840 + (bid >> 1) * 32 + (tid & 3) * 8;
#pragma unroll
            for (int i = 0; i < 5; ++i) cv[i] = P.c[r0 + i * 64];
#pragma unroll
            for (int i = 0; i < 5; ++i) mv[i] = ldg_nc256(s + (size_t)i * 64 * 3840);
        }
        if (bid >= 28) {
            const __nv_bfloat16* s = P.wqkv + (size_t)(rp_kc * 64 + (tid >> 5) * 8 + (lane >> 3)) * 1920 + 640 + rp_line * 64 + (lane & 7) * 8;
            kr[0] = ldg_nc(s); kr[1] = ldg_nc(s + 4 * 1920);
        }
    }
    Scratch& S = *P.s;
    uint32_t ep = ld_flag(&S.g_epoch);
    extern __shared__ __align__(1024) unsigned char smem[];
    constexpr uint32_t sb = 1024;
    const int warp = __shfl_sync(~0u, tid >> 5, 0);
    const int rb = (bid >> 5) * 4 + ((bid & 15) >> 2);
    const int hg = ((bid >> 4) & 1) * 4 + (bid & 3);
    const int rb64 = rb * 2 + (hg >> 2), cg = hg & 3;
    auto BAR = [&](int i) { return sb + OFF_BAR + i * 8; };

    if (warp >= 8) {
        asm volatile("setmaxnreg.dec.sync.aligned.u32 40;");
        const int at = tid - 256, aw = warp - 8;
        if (smem_u32(smem) != sb) __trap();
        if (at == 0) {
            asm volatile("prefetch.tensormap [%0];" ::"l"(&M.x) : "memory");
            for (int i = 0; i < 10; ++i) { mbar_init(BAR(B_X + i), 1); mbar_arrive_tx(BAR(B_X + i), 16384); }
            fence_async_smem();
        } else if (at == 32) {
            for (int i = 0; i < NSLOT; ++i) { mbar_init(BAR(B_FULL + i), 1); mbar_init(BAR(B_EMPTY + i), 8); }
            for (int i = 0; i < 8; ++i) mbar_init(BAR(B_WO + i), 1);
            mbar_init(BAR(B_STG), 1); mbar_init(BAR(B_STG + 1), 1);
            mbar_init(BAR(B_KREM), 1); mbar_init(BAR(B_VREM), 1); mbar_init(BAR(B_KOWN), 8);
            mbar_init(BAR(B_VOWN), 8); mbar_init(BAR(B_HP0), 8); mbar_init(BAR(B_ATT), 8); mbar_init(BAR(B_MOD2), 64);
            mbar_init(BAR(B_WODONE), 8); mbar_init(BAR(B_GU), 1); mbar_init(BAR(B_DN), 1); mbar_init(BAR(B_TOP), 1);
            mbar_init(BAR(B_KREP), 8); mbar_init(BAR(B_XDONE), 8); mbar_init(BAR(B_FFN), 1);
            mbar_init(BAR(B_MSTG), 1); mbar_init(BAR(B_MSTG2), 1); mbar_init(BAR(B_MFREE), 2);
            mbar_arrive_tx(BAR(B_MSTG), 20480); mbar_arrive_tx(BAR(B_MSTG2), 20480);
            fence_async_smem();
        }
        bar_sync(0, NTHR);
        if (aw == 0) {
            if (lane < 10) tma_2d(sb + OFF_X + lane * 16384, &M.x, lane * 64, rb * 128, BAR(B_X + lane));
        }
        ep += 1;
        if (aw == 0) {
            if (bid >= 28) {
                mbar_wait(BAR(B_KREP), 0);
                if (lane == 0) st_flag(&S.g_wflag[rp_line * 16 + rp_kc], ep);
            }
            TS(0);
            const uint32_t* fl = S.g_wflag + (((hg * 10) >> 3) + (lane >> 4)) * 16 + min(lane & 15, 9);
            const unsigned char* src = reinterpret_cast<const unsigned char*>(S.g_wq) + (size_t)hg * 15 * CHUNK_B;
            uint32_t it = 0;
#pragma unroll 1
            for (int c = 0; c < 15; ++c) {
                if (c == 0 || c == 5 || c == 10) {
                    while (!__all_sync(~0u, ld_flag(fl) == ep) && ++it < SPIN_MAX) { }
                    fl += 160;
                }
                if (c == 0) TS(1);
                if (c >= NSLOT) mbar_wait(BAR(B_EMPTY + (c & 3)), ((c >> 2) - 1) & 1);
                else if (c == 2) mbar_wait(BAR(B_XDONE), 0);
                if (lane == 0) {
                    mbar_arrive_tx(BAR(B_FULL + (c & 3)), CHUNK_B);
                    bulk_g2s(sb + OFF_RING + (c & 3) * CHUNK_B, src, CHUNK_B, BAR(B_FULL + (c & 3)));
                }
                if (c >= 4 && c < 12 && lane == 1 && bid < 80)
                    tma_2d(sb + OFF_KV + (c & 1) * KVR + ((c - 4) >> 1) * KVH + KP, &M.m, 1280 + bid * 32, ((c & 1) * 4 + ((c - 4) >> 1)) * 80, BAR(B_MSTG + (c >> 3)));
                src += CHUNK_B;
            }
            TS(2);
            {
                const uint4* wf = reinterpret_cast<const uint4*>(S.g_woflag + (cg >> 1) * 96) + (lane < 20 ? lane : 0);
                uint4 f;
                it = 0;
                do { f = ld_ll16(wf); } while (!__all_sync(~0u, f.x == ep && f.y == ep && f.z == ep && f.w == ep) && ++it < SPIN_MAX);
            }
            const unsigned char* wsrc = reinterpret_cast<const unsigned char*>(S.g_wo) + (size_t)(cg * 40 + (lane & 1) * 20) * WOSTEP_B;
            const uint32_t wbar = BAR(B_WO + (lane & 1) * 4);
            mbar_wait(BAR(B_EMPTY + 2), 1);
            if (lane < 2) {
                mbar_arrive_tx(wbar, 8 * WOSTEP_B);
                bulk_g2s(sb + OFF_RING + lane * 8 * WOSTEP_B, wsrc, 8 * WOSTEP_B, wbar);
            }
            TS(3);
            mbar_wait(BAR(B_HP0), 0);
            if (lane < 2) {
                mbar_arrive_tx(wbar + 8, 6 * WOSTEP_B);
                bulk_g2s(sb + OFF_KV + lane * 6 * WOSTEP_B, wsrc + 8 * WOSTEP_B, 6 * WOSTEP_B, wbar + 8);
            }
            mbar_wait(BAR(B_ATT), 0);
            if (lane < 4) {
                const int q = lane >> 1;
                mbar_arrive_tx(wbar + 16 + q * 8, 3 * WOSTEP_B);
                bulk_g2s(sb + OFF_KV + KVR + ((lane & 1) * 6 + q * 3) * WOSTEP_B, wsrc + (14 + q * 3) * WOSTEP_B, 3 * WOSTEP_B, wbar + 16 + q * 8);
            }
            TS(4);
            mbar_wait(BAR(B_FFN), 0);
            TS(5);
            mbar_wait(BAR(B_WODONE), 0);
            if (lane == 0 && bid < 96) {
                mbar_arrive_tx(BAR(B_GU), 40960);
                bulk_g2s(sb + OFF_GU, S.g_gu + bid * 2560, 40960, BAR(B_GU));
            }
            if (lane == 1 && bid >= 88) {
                mbar_arrive_tx(BAR(B_DN), 49152);
                bulk_g2s(sb + OFF_DN, S.g_dn + (bid - 88) * 3072, 49152, BAR(B_DN));
            }
        } else {
            if (aw == 1) {
                const int first = rb >= 2 ? 0 : 4 - rb * 2;
                unsigned char* gk = reinterpret_cast<unsigned char*>(S.g_kv) + (ptrdiff_t)(hg * 32 + rb * 2 - 4 + (lane >> 1)) * (2 * KVH);
                const uint32_t sk = sb + OFF_KV + (lane & 1) * KVR + (lane >> 1) * KVH;
#pragma unroll 1
                for (int kv = 0; kv < 2; ++kv) {
                    const uint32_t bar = BAR(B_KREM + kv);
                    const uint32_t bytes = kv == 0 ? KP : VP;
                    const uint32_t goff = kv * 2 * KP + (lane & 1) * bytes;
                    if (kv) {
                        mbar_wait(BAR(B_MFREE), 0);
                        for (int b = 0; b < first * 2; ++b)
                            for (int i = lane; i < VP / 16; i += 32)
                                *reinterpret_cast<uint4*>(smem + OFF_KV + (b & 1) * KVR + (b >> 1) * KVH + KP + i * 16) = make_uint4(0, 0, 0, 0);
                        fence_async_smem();
                        __syncwarp();
                    }
                    if (lane == 0) mbar_arrive_tx(bar, bytes * 2 * (4 - first));
                    mbar_wait(BAR(B_KOWN + kv), 0);
                    if (lane >= 8 && lane < 12) {
                        bulk_s2g(gk + goff, sk + kv * KP, bytes);
                        bulk_commit_wait();
                    }
                    __syncwarp();
                    if (lane == 0) st_flag(&S.g_kvflag[(hg * 16 + rb) * 32 + kv], ep);
                    TS(1 + 2 * kv);
                    if (lane < 8 && lane >= first * 2) {
                        const uint32_t* fp = &S.g_kvflag[(hg * 16 + rb - 2 + (lane >> 2)) * 32 + kv];
                        uint32_t it = 0;
                        while (ld_flag(fp) != ep && ++it < SPIN_MAX) { }
                        bulk_g2s(sk + kv * KP, gk + goff, bytes, bar);
                    }
                    __syncwarp();
                    TS(2 + 2 * kv);
                }
                {
                    uint4* z = &S.g_o[(size_t)((((~ep & 1) * 32 + rb * 2) * 4) * 40 + hg * 5) * 32 + lane];
#pragma unroll 1
                    for (int i = 0; i < 8; ++i)
#pragma unroll
                        for (int u = 0; u < 5; ++u) z[(i * 40 + u) * 32] = make_uint4(0, 0, 0, 0);
                }
                if (lane == 0) {
                    const int b0 = bid < 96 ? 0 : 10, b1 = bid >= 88 ? 22 : 10;
                    auto pref = [&](int b) {
                        const int m = b < 5 ? 0 : b < 10 ? 1 : 2;
                        if (b < b1)
                            asm volatile("cp.async.bulk.prefetch.tensor.2d.L2.global [%0, {%1,%2}];" ::"l"(&M.w[m]), "r"((m < 2 ? bid : bid - 88) * 16), "r"((b - m * 5) * 128) : "memory");
                    };
                    auto issue = [&](int b) {
                        const int m = b < 5 ? 0 : b < 10 ? 1 : 2;
                        pref(b + 2);
                        mbar_arrive_tx(BAR(B_STG + (b & 1)), 4096);
                        tma_2d(sb + OFF_STG + (b & 1) * 4096, &M.w[m], (m < 2 ? bid : bid - 88) * 16, (b - m * 5) * 128, BAR(B_STG + (b & 1)));
                    };
                    issue(b0);
#pragma unroll 1
                    for (int b = b0; b < b1; ++b) {
                        if (b + 1 < b1) {
                            asm volatile("cp.async.bulk.wait_group.read 0;" ::: "memory");
                            issue(b + 1);
                        }
                        mbar_wait(BAR(B_STG + (b & 1)), ((b - b0) >> 1) & 1);
                        bulk_s2g(b < 10 ? S.g_gu + bid * 2560 + b * 256 : S.g_dn + (bid - 88) * 3072 + (b - 10) * 256, sb + OFF_STG + (b & 1) * 4096, 4096);
                        asm volatile("cp.async.bulk.commit_group;" ::: "memory");
                    }
                    asm volatile("cp.async.bulk.wait_group 0;" ::: "memory");
                    mbar_arrive(BAR(B_FFN));
                }
                TS(5);
            } else {
                const int a2 = aw - 2;
                mbar_wait(BAR(B_X + VQ_AFTER), 0);
                TS(0);
                if (bid >= 28) {
                    const int cc = rp_line * 8 + (lane & 7), hh = cc / 10;
                    const __nv_bfloat16* s = P.wqkv + (size_t)(rp_kc * 64 + a2 * 32 + (lane >> 3)) * 1920 + cc * 8;
                    uint4* d = S.g_wq + (size_t)(hh * 240 + rp_kc * 8 + a2 * 4) * 80 + (cc - hh * 10) * 8 + (lane >> 3);
                    uint32_t chk = 0;
#pragma unroll 1
                    for (int q = 0; q < 4; ++q) {
                        const int p = 1 + (q >> 1), hf = q & 1;
                        uint4 v[4];
#pragma unroll
                        for (int i = 0; i < 4; ++i) v[i] = ldg_nc(s + (size_t)(hf * 16 + i * 4) * 1920 + (p == 1 ? 1280 : 0));
#pragma unroll
                        for (int i = 0; i < 4; ++i) { d[(p * 80 + hf * 2 + (i >> 1)) * 80 + (i & 1) * 4] = v[i]; chk += v[i].x; }
                        if (hf) {
                            uint32_t rbk, it = 0;
                            do {
                                rbk = 0;
#pragma unroll
                                for (int i = 0; i < 8; ++i) rbk += ld_flag(d + (p * 80 + (i >> 1)) * 80 + (i & 1) * 4);
                            } while (rbk != chk && ++it < SPIN_MAX);
                            chk = 0;
                            bar_sync(7, 64);
                            if (at == 64) st_flag(&S.g_wflag[p * 160 + rp_line * 16 + rp_kc], ep);
                        }
                    }
                }
                TS(1);
                if (bid >= 48) {
                    const int k8 = bid - 48, hs = k8 / 10, pos = (int)((0x7695432810ull >> (4 * (k8 - hs * 10))) & 15);
                    const __nv_bfloat16* s = P.wo + (size_t)(k8 * 8 + (lane >> 2)) * DM + a2 * 320 + (lane & 3) * 8;
                    uint32_t* d = reinterpret_cast<uint32_t*>(S.g_wo) + (size_t)a2 * 2 * 51200 + (hs * 10 + pos) * 640 + lane;
#pragma unroll 1
                    for (int q = 0; q < 2; ++q) {
                        uint4 v[5];
#pragma unroll
                        for (int i = 0; i < 5; ++i) v[i] = ldg_nc(s + q * 160 + i * 32);
#pragma unroll
                        for (int i = 0; i < 5; ++i) {
                            uint32_t* dd = d + q * 51200 + i * 128;
                            dd[0] = v[i].x; dd[32] = v[i].y; dd[64] = v[i].z; dd[96] = v[i].w;
                        }
                    }
                    __syncwarp();
                    if (lane == 0) { fence_gpu(); st_flag(&S.g_woflag[a2 * 96 + k8], ep); }
                }
                TS(2);
                if (bid < 80) {
                    float* sl = reinterpret_cast<float*>(smem + OFF_RED) + a2 * 320;
#pragma unroll
                    for (int i = 0; i < 10; ++i) sl[lane + 32 * i] = silu_bf(P.c[a2 * 320 + lane + 32 * i]);
                    __syncwarp();
                    sl += lane >> 2;
                    const uint4* s = reinterpret_cast<const uint4*>(smem + OFF_KV + a2 * KVR + KP) + lane;
                    float acc[8];
#pragma unroll
                    for (int i = 0; i < 8; ++i) acc[i] = 0.f;
#pragma unroll 1
                    for (int bt = 0; bt < 8; ++bt) {
                        mbar_wait(BAR(B_MSTG + (bt >> 2)), 0);
#pragma unroll
                        for (int i = 0; i < 5; ++i) fma8(acc, sl[i * 8], s[i * 32]);
                        s += (bt & 1) ? KVH / 16 - 160 : 160; sl += 40;
                    }
                    __syncwarp();
                    if (lane == 0) mbar_arrive(BAR(B_MFREE));
                    float r = treduce8(acc, lane);
                    float* red2 = reinterpret_cast<float*>(smem + OFF_RED2);
                    if (a2 == 1) red2[lane] = r;
                    bar_sync(7, 64);
                    if (a2 == 0) {
                        r = rbf(r + red2[lane]);
                        const int pr = (lane & 3) * 4 + ((lane >> 2) & 1) * 2 + ((lane >> 3) & 1);
                        const float hi = __shfl_xor_sync(~0u, r, 16);
                        if (lane < 16) st_ll8(&S.g_mod[bid * 16 + pr], pack_bf16(r, hi), ep);
                        if (bid >= 20 && bid < 60) {
                            float q = (bid < 40 ? r : rbf(1.0f + r)) * __bfloat162float(P.wr[(bid % 20) * 32 + pr * 2 + (lane >> 4)]);
#pragma unroll
                            for (int o = 16; o > 0; o >>= 1) q += __shfl_xor_sync(~0u, q, o);
                            if (lane == 0) st_ll8(&S.g_msum[bid - 20], __float_as_uint(q), ep);
                        }
                    }
                }
                else if (lane == 0) mbar_arrive(BAR(B_MFREE));
                TS(3);
                {
                    const int i = at - 64;
                    const uint2* p0 = i < 40 ? &S.g_mod[cg * 80 + 2 * i] : i < 60 ? &S.g_msum[2 * (i - 40)] : &S.g_mod[960 + max(bid - 88, 0) * 8 + 2 * (i - 60)];
                    const int st = i < 40 ? 320 : 0;
                    const uint2 wr = reinterpret_cast<const uint2*>(P.wr)[cg * 40 + min(i, 39)];
                    uint4 va, vs, vc, vg;
                    uint32_t it = 0;
                    do {
                        va = ld_ll16(p0); vs = ld_ll16(p0 + st); vc = ld_ll16(p0 + 2 * st); vg = ld_ll16(p0 + 3 * st);
                    } while (!(va.y == ep && va.w == ep && vs.y == ep && vs.w == ep && vc.y == ep && vc.w == ep && vg.y == ep && vg.w == ep) && ++it < SPIN_MAX);
                    __syncwarp();
                    if (i < 40) {
                        const uint32_t c0 = pack_bf16(1.0f + bf_lo(vc.x), 1.0f + bf_hi(vc.x)), c1 = pack_bf16(1.0f + bf_lo(vc.z), 1.0f + bf_hi(vc.z));
                        uint2* tb = reinterpret_cast<uint2*>(smem + OFF_TAB) + i;
                        tb[0] = make_uint2(va.x, va.z); tb[40] = make_uint2(c0, c1); tb[80] = make_uint2(vs.x, vs.z); tb[120] = make_uint2(vg.x, vg.z);
                        uint32_t* tw = reinterpret_cast<uint32_t*>(smem + OFF_TABW) + (i >> 3) * 64 + (i & 7);
#pragma unroll
                        for (int e = 0; e < 2; ++e) {
                            const uint32_t cc = e ? c1 : c0, ww = e ? wr.y : wr.x;
                            const float g0 = bf_lo(cc) * bf_lo(ww), g1 = bf_hi(cc) * bf_hi(ww);
                            const uint32_t hi = pack_bf16(g0, g1);
                            tw[e * 8] = 0x3F803F80u; tw[e * 8 + 16] = hi; tw[e * 8 + 32] = pack_bf16(g0 - bf_lo(hi), g1 - bf_hi(hi)); tw[e * 8 + 48] = 0u;
                        }
                    } else if (i >= 60) {
                        reinterpret_cast<float4*>(smem + OFF_GBD)[i - 60] = make_float4(bf_lo(va.x), bf_hi(va.x), bf_lo(va.z), bf_hi(va.z));
                    }
                    if (a2 == 1) {
                        const float q = __uint_as_float(va.x) + __uint_as_float(va.z);
                        float sbw = (i >= 40 && i < 50) ? q : 0.f, sg = (i >= 50 && i < 60) ? q : 0.f;
#pragma unroll
                        for (int o = 16; o > 0; o >>= 1) { sg += __shfl_xor_sync(~0u, sg, o); sbw += __shfl_xor_sync(~0u, sbw, o); }
                        if (lane == 0) *reinterpret_cast<float2*>(smem + OFF_CONST) = make_float2(sg, sbw);
                    }
                    mbar_arrive(BAR(B_MOD2));
                    TS(4);
                }
                if (a2 == 1) {
                    mbar_wait(BAR(B_WODONE), 0);
                    uint4 cnd;
                    uint32_t it = 0;
                    do { cnd = ld_ll16(&S.g_cand[lane * 8]); } while (!(cnd.y == ep && cnd.w == ep) && ++it < SPIN_MAX);
                    const uint32_t k1 = __reduce_max_sync(~0u, cnd.x);
                    const uint32_t k2 = __reduce_max_sync(~0u, cnd.x == k1 ? cnd.z : cnd.x);
                    if (lane == 0) {
                        *reinterpret_cast<uint2*>(smem + OFF_CAND + 64) = make_uint2(k1, k2);
                        mbar_arrive(BAR(B_TOP));
                        if (bid == 0) S.g_epoch = ep;
                    }
                    TS(5);
                }
            }
        }
    } else {
        const int wg = warp >> 2, w = warp & 3, g = lane >> 2, t = lane & 3;
        {
            const int cc = rp_line * 8 + (lane & 7), hh = cc / 10;
            float sl[5];
            if (bid < 80) {
#pragma unroll
                for (int i = 0; i < 5; ++i) sl[i] = silu_bf(cv[i]);
            }
            bar_sync(0, NTHR);
            TS(20);
            uint4* d = S.g_wq + (size_t)(hh * 240 + rp_kc * 8 + warp) * 80 + (cc - hh * 10) * 8 + (lane >> 3);
            if (bid >= 28) {
                d[0] = kr[0]; d[4] = kr[1];
                kr[0].y = ld_flag(d); kr[1].y = ld_flag(d + 4);
                TS(21);
            }
            ep += 1;
            if (bid < 80) {
                float acc[8];
#pragma unroll
                for (int i = 0; i < 8; ++i) acc[i] = 0.f;
#pragma unroll
                for (int i = 0; i < 5; ++i) fma8(acc, sl[i], mv[i]);
                float* red = reinterpret_cast<float*>(smem + OFF_RED);
                red[warp * 32 + lane] = treduce8(acc, lane);
                TS(22);
                bar_sync(6, 256);
                if (warp == 0) {
                    float r = 0.f;
#pragma unroll
                    for (int i = 0; i < 8; ++i) r += red[i * 32 + lane];
                    const uint32_t lo = ((__float_as_uint(r) + 0x80u) & ~0xFFu) | ((lane < 16 ? ep : ep >> 8) & 0xFFu);
                    const uint32_t hi = __shfl_xor_sync(~0u, lo, 16);
                    if (lane < 16)
                        st_ll8(reinterpret_cast<uint2*>(&S.g_mod1[(bid >> 1) * 16 + t * 4 + ((lane >> 2) & 1) * 2 + (lane >> 3)]) + (bid & 1), lo, hi);
                }
            }
            if (bid >= 28) {
                uint32_t it = 0;
                while ((kr[0].y != kr[0].x || kr[1].y != kr[1].x) && ++it < SPIN_MAX) { kr[0].y = ld_flag(d); kr[1].y = ld_flag(d + 4); }
                __syncwarp();
                if (lane == 0) mbar_arrive(BAR(B_KREP));
            }
            asm volatile("setmaxnreg.inc.sync.aligned.u32 232;");
            TS(19);
        }
        uint32_t qf[20];
        {
            uint32_t a[160];
            uint32_t lr[2], ln[2];
            {
                float cs_[2][4], qa[2][4], qb[2][4];
#pragma unroll
                for (int i = 0; i < 8; ++i) cs_[i >> 2][i & 3] = qa[i >> 2][i & 3] = qb[i >> 2][i & 3] = 0.f;
                const uint32_t xa = sb + OFF_X + (warp * 16 + (lane & 15)) * 128;
                uint32_t xo[4];
                const uint4* mp = &S.g_mod1[tid];
#pragma unroll
                for (int s = 0; s < 4; ++s) xo[s] = xa + (((2 * s + (lane >> 4)) ^ (lane & 7)) << 4);
#pragma unroll
                for (int kc = 0; kc < 10; ++kc) {
                    if (kc == MOD_AT) {
#pragma unroll
                        for (int i = 0; i < 3; ++i) mv[i] = ld_ll16(mp + i * (i == 2 && wg ? 128 : 256));
                    }
                    mbar_wait(BAR(B_X + kc), 0);
                    if (kc == 0) TS(23);
                    if (kc == 4) TS(24);
                    if (kc == 9) TS(25);
#pragma unroll
                    for (int s = 0; s < 4; ++s) {
                        const int o = (kc * 4 + s) * 4;
                        ldmatrix4(a[o], a[o + 1], a[o + 2], a[o + 3], xo[s] + kc * 16384);
                    }
#pragma unroll
                    for (int s = 0; s < 4; ++s) {
                        const int o = (kc * 4 + s) * 4;
                        const uint32_t wq[4] = {a[o], a[o + 1], a[o + 2], a[o + 3]};
                        mma16816(cs_[s & 1], wq, 0x3F803F80u, 0x3F803F80u);
                        mma16816(qa[s & 1], wq, wq[0], wq[2]);
                        mma16816(qb[s & 1], wq, wq[1], wq[3]);
                    }
                }
                if (lane == 0) mbar_arrive(BAR(B_XDONE));
#pragma unroll
                for (int r = 0; r < 2; ++r) {
                    float dg = 0.f;
#pragma unroll
                    for (int i = 0; i < 2; ++i) dg += r == 0 ? ((g & 1) ? qa[i][1] : qa[i][0]) : ((g & 1) ? qb[i][3] : qb[i][2]);
                    const float v = __shfl_sync(~0u, dg, (lane & ~3) + (g >> 1));
                    const float mean = (cs_[0][2 * r] + cs_[1][2 * r]) * (1.0f / DM);
                    const float var = fmaxf(v * (1.0f / DM) - mean * mean, 0.f);
                    const float rs = rsqrtf(var + 1e-5f);
                    lr[r] = pack_bf16(rs, rs);
                    ln[r] = pack_bf16(-mean * bf_lo(lr[r]), -mean * bf_lo(lr[r]));
                }
            }
            TS(0);
            {
                const uint32_t e = ep;
                const uint4* mp = &S.g_mod1[tid];
                uint32_t it = 0;
                for (;;) {
                    bool ok = true;
#pragma unroll
                    for (int i = 0; i < 3; ++i)
                        ok = ok && __byte_perm(mv[i].x, mv[i].y, 0x4440) == __byte_perm(e, 0, 0x1110) && __byte_perm(mv[i].z, mv[i].w, 0x4440) == __byte_perm(e, 0, 0x1110);
                    if (ok || ++it >= SPIN_MAX) break;
#pragma unroll
                    for (int i = 0; i < 3; ++i) mv[i] = ld_ll16(mp + i * (i == 2 && wg ? 128 : 256));
                }
                uint32_t* mt = reinterpret_cast<uint32_t*>(smem + OFF_MT);
#pragma unroll
                for (int i = 0; i < 3; ++i) {
                    const int p = tid + i * (i == 2 && wg ? 128 : 256), q = p < 320 ? p : p - 320;
                    uint32_t m = pack_bf16(__uint_as_float(mv[i].x & ~0xFFu) + __uint_as_float(mv[i].z & ~0xFFu),
                                           __uint_as_float(mv[i].y & ~0xFFu) + __uint_as_float(mv[i].w & ~0xFFu));
                    if (p >= 320) m = hadd2_bf16(m, 0x3F803F80u);
                    mt[((q >> 3) * 4 + (q & 3)) * 4 + ((q >> 2) & 1) + (p < 320 ? 2 : 0)] = m;
                }
                bar_sync(6, 256);
            }
            TS(1);
            float acc[40];
            uint4 mt[4];
            uint32_t mta = sb + OFF_MT + t * 16;
            auto ld_mt = [&]() { lds128<0>(mt[0], mta); lds128<64>(mt[1], mta); lds128<128>(mt[2], mta); lds128<192>(mt[3], mta); asm volatile("add.u32 %0, %0, 256;" : "+r"(mta)); };
            [[maybe_unused]] uint32_t twait = 1;
            const uint64_t dring = mkdesc(sb + OFF_RING, 1280, 128);
            const uint32_t stb = sb + OFF_KV + (4 + wg) * KVH + (w * 16 + (lane & 15)) * 16;
            const uint32_t st0 = stb + (lane >> 4) * 1024, st2 = stb + ((lane >> 4) ? KVR : 4096);
#pragma unroll
            for (int p = 0; p < 3; ++p) {
#pragma unroll
                for (int kc = 0; kc < 10; ++kc) {
                    const int c = p * 5 + (kc >> 1), slot = c & 3;
                    if (p == 0) {
                        if (kc == 0) ld_mt();
#pragma unroll
                        for (int i = 0; i < 16; ++i) hfma2_ip(a[kc * 16 + i], lr[i & 1], ln[i & 1]);
#pragma unroll
                        for (int i = 0; i < 16; ++i) hfma2_ip(a[kc * 16 + i], (i & 2) ? mt[i >> 2].y : mt[i >> 2].x, (i & 2) ? mt[i >> 2].w : mt[i >> 2].z);
                        if (kc < 9) ld_mt();
                    }
                    if (!(kc & 1)) TW(twait, mbar_wait(BAR(B_FULL + slot), (c >> 2) & 1));
                    if (p == 0 || !(kc & 1)) WG_FENCE();
#pragma unroll
                    for (int s = 0; s < 4; ++s) {
                        const int o = (kc * 4 + s) * 4;
                        const uint64_t db = dring + (uint64_t)((slot * CHUNK_B + ((kc & 1) * 4 + s) * 2560) >> 4);
                        if (kc == 0 && s == 0) wgmma_n80_init(acc, a[o], a[o + 1], a[o + 2], a[o + 3], db);
                        else wgmma_n80(acc, a[o], a[o + 1], a[o + 2], a[o + 3], db);
                    }
                    WG_COMMIT();
                    if (kc > 0 && !(kc & 1)) {
                        WG_WAIT(1);
                        if (lane == 0) mbar_arrive(BAR(B_EMPTY + ((c - 1) & 3)));
                    }
                }
                WG_WAIT(0);
                pin(acc);
                if (lane == 0) mbar_arrive(BAR(B_EMPTY + ((p * 5 + 4) & 3)));
                TS(2 + p);
                TSV(26 + p, twait);
                if (p == 0) {
#pragma unroll
                    for (int jj = 0; jj < 5; ++jj)
                        stmatrix4(jj < 2 ? st0 + jj * 2048 : (jj == 2 ? st2 : st0 + KVR + (2 * jj - 5) * 1024),
                                  pack_bf16(acc[8 * jj + 0], acc[8 * jj + 1]), pack_bf16(acc[8 * jj + 2], acc[8 * jj + 3]),
                                  pack_bf16(acc[8 * jj + 4], acc[8 * jj + 5]), pack_bf16(acc[8 * jj + 6], acc[8 * jj + 7]));
                    fence_async_smem();
                    __syncwarp();
                    if (lane == 0) mbar_arrive(BAR(B_KOWN));
                } else if (p == 1) {
                    uint32_t vt[24];
#pragma unroll
                    for (int hp = 0; hp < 2; ++hp) {
#pragma unroll
                        for (int r = 0; r < 2; ++r) {
                            auto pk = [&](int j) { return pack_bf16(acc[4 * j + 2 * r], acc[4 * j + 2 * r + 1]); };
                            const uint32_t mid = pk(5 * hp + 2);
                            vt[(6 * hp + 0) * 2 + r] = pk(5 * hp + 0);
                            vt[(6 * hp + 1) * 2 + r] = pk(5 * hp + 1);
                            vt[(6 * hp + 2) * 2 + r] = t < 2 ? mid : (t == 2 ? 0x00003F80u : 0u);
                            vt[(6 * hp + 3) * 2 + r] = pk(5 * hp + 3);
                            vt[(6 * hp + 4) * 2 + r] = pk(5 * hp + 4);
                            vt[(6 * hp + 5) * 2 + r] = t >= 2 ? mid : (t == 0 ? 0x00003F80u : 0u);
                        }
                    }
#pragma unroll
                    for (int jj = 0; jj < 6; ++jj)
                        stmatrix4(st0 + (jj / 3) * KVR + KP + (jj % 3) * 2048, vt[4 * jj], vt[4 * jj + 1], vt[4 * jj + 2], vt[4 * jj + 3]);
                    fence_async_smem();
                    __syncwarp();
                    if (lane == 0) mbar_arrive(BAR(B_VOWN));
                } else {
#pragma unroll
                    for (int i = 0; i < 20; ++i) qf[i] = pack_bf16(acc[2 * i], acc[2 * i + 1]);
                }
            }
        }
        {
            uint32_t qh[24];
#pragma unroll
            for (int h = 0; h < 4; ++h) {
                const int jb = (h >> 1) * 5 + (h & 1) * 3, xb = (h >> 1) * 5 + 2;
                const bool keep = (h & 1) ? (t >= 2) : (t < 2);
#pragma unroll
                for (int i = 0; i < 4; ++i) qh[h * 6 + i] = qf[2 * jb + i];
                qh[h * 6 + 4] = keep ? qf[2 * xb] : 0u;
                qh[h * 6 + 5] = keep ? qf[2 * xb + 1] : 0u;
            }
            const int bmin = 4 - min(4, rb * 2 + wg);
            const int thr = w * 16 + g - 2 * t;
            uint32_t msk[9];
#pragma unroll
            for (int k = 0; k < 9; ++k) msk[k] = ((8 * (k - 1) > thr) ? 0xFFFFu : 0u) | ((8 * (k - 1) + 1 > thr) ? 0xFFFF0000u : 0u);
            const float cs = 0.22360679774997896f * 1.4426950408889634f;
            uint4* go = &S.g_o[(size_t)((((ep & 1) * 32 + rb * 2 + wg) * 4 + w) * 40 + hg * 5) * 32 + lane];
            const bool sw = hg >= 4;
            uint32_t oa0 = 0, oa1 = 0, oc0 = 0, oc1 = 0;
            mbar_wait(BAR(B_VOWN), 0);
            mbar_wait(BAR(B_KREM), 0);
            TS(5);
            if (wg == 1) bar_arrive(4, 256);
#pragma unroll 1
            for (int h = 0; h < 4; ++h) {
                const uint32_t kvb = sb + OFF_KV + wg * KVH + (h >> 1) * KVR;
                const uint64_t dke = mkdesc(kvb + 2048, 1024, 128);
                const uint64_t dk = mkdesc(kvb + (h & 1) * 3072, 1024, 128), dv = mkdesc(kvb + KP + (h & 1) * 3072, 128, 1024);
                float sc[5][32];
                WG_FENCE();
#pragma unroll
                for (int b = 0; b < 5; ++b) {
                    wgmma_n64_init(sc[b], qh[0], qh[1], qh[2], qh[3], dk + (uint64_t)((b * KVH) >> 4));
                    wgmma_n64(sc[b], qh[4], qh[5], 0u, 0u, dke + (uint64_t)((b * KVH) >> 4));
                }
                WG_COMMIT();
                WG_WAIT(0);
#pragma unroll
                for (int b = 0; b < 5; ++b) pin(sc[b]);
#pragma unroll
                for (int i = 0; i < 18; ++i) qh[i] = qh[i + 6];
                if (__builtin_expect(bmin > 0, 0)) {
#pragma unroll
                    for (int b = 0; b < 4; ++b)
                        if (b < bmin) {
#pragma unroll
                            for (int i = 0; i < 32; ++i) asm volatile("mov.b32 %0, 0xFF800000;" : "=f"(sc[b][i]));
                        }
                }
#pragma unroll
                for (int i = 0; i < 32; ++i) {
                    const int cc = 8 * (i >> 2) + (i & 1) - 8 * ((i >> 1) & 1);
                    sc[0][i] = cc > thr ? sc[0][i] : sc[4][i];
                }
                float mx[2][4];
#pragma unroll
                for (int b = 0; b < 4; ++b) {
                    mx[0][b] = fmaxf(sc[b][0], sc[b][1]); mx[1][b] = fmaxf(sc[b][2], sc[b][3]);
#pragma unroll
                    for (int i = 4; i < 32; ++i) mx[(i >> 1) & 1][b] = fmaxf(mx[(i >> 1) & 1][b], sc[b][i]);
                }
                float mc[2];
#pragma unroll
                for (int r = 0; r < 2; ++r) {
                    float m = fmaxf(fmaxf(mx[r][0], mx[r][1]), fmaxf(mx[r][2], mx[r][3]));
                    m = fmaxf(m, __shfl_xor_sync(~0u, m, 1));
                    m = fmaxf(m, __shfl_xor_sync(~0u, m, 2));
                    mc[r] = -m * cs;
                }
                mbar_wait(BAR(B_VREM), 0);
                float o[12];
                bar_sync(4 + wg, 256);
#pragma unroll
                for (int b = 0; b < 4; ++b) {
                    uint32_t pp[16];
#pragma unroll
                    for (int i = 0; i < 16; ++i)
                        pp[i] = pack_bf16(ex2(fmaf(sc[b][2 * i], cs, mc[i & 1])), ex2(fmaf(sc[b][2 * i + 1], cs, mc[i & 1])));
                    if (b == 3 && wg + h < 4) bar_arrive(5 - wg, 256);
                    if (b == 0) {
                        uint32_t pn[16];
#pragma unroll
                        for (int i = 0; i < 16; ++i) {
                            const uint32_t m = msk[(i >> 1) - (i & 1) + 1];
                            pn[i] = pp[i] & ~m; pp[i] &= m;
                        }
                        WG_FENCE();
#pragma unroll
                        for (int kk = 0; kk < 4; ++kk) {
                            const uint64_t d = dv + (uint64_t)((4 * KVH + kk * 256) >> 4);
                            if (kk == 0) wgmma_n24_init(o, pn[0], pn[1], pn[2], pn[3], d);
                            else wgmma_n24(o, pn[4 * kk], pn[4 * kk + 1], pn[4 * kk + 2], pn[4 * kk + 3], d);
                        }
                    } else {
                        WG_FENCE();
                    }
#pragma unroll
                    for (int kk = 0; kk < 4; ++kk)
                        wgmma_n24(o, pp[4 * kk], pp[4 * kk + 1], pp[4 * kk + 2], pp[4 * kk + 3], dv + (uint64_t)((b * KVH + kk * 256) >> 4));
                    WG_COMMIT();
                }
                WG_WAIT(0);
                pin(o);
                if ((h & 1) && lane == 0) mbar_arrive(BAR(B_HP0) + (h >> 1) * 8);
                const int src = (lane & ~3) + ((h & 1) ? 0 : 2);
                const float i0 = rcp(__shfl_sync(~0u, o[8], src)), i1 = rcp(__shfl_sync(~0u, o[10], src));
                uint32_t po[6];
#pragma unroll
                for (int i = 0; i < 3; ++i) {
                    const uint32_t r0 = pack_bf16(o[4 * i] * i0, o[4 * i + 1] * i0), r1 = pack_bf16(o[4 * i + 2] * i1, o[4 * i + 3] * i1);
                    po[2 * i] = sw ? r1 : r0; po[2 * i + 1] = sw ? r0 : r1;
                }
                st_b128(go + h * 32, po[0] ? po[0] : 0x8000u, po[1], po[2], po[3]);
                if (h == 2) { oa0 = oc0; oa1 = oc1; }
                if (!(h & 1) || t >= 2) { oc0 = po[4]; oc1 = po[5]; }
                TS(6 + h);
            }
            st_b128(go + 4 * 32, oa0 ? oa0 : 0x8000u, oa1, oc0, oc1);
        }
        const int row = rb64 * 64 + w * 16 + g + 8 * wg;
        uint32_t x1[20];
        {
            const __nv_bfloat16* xp = P.x + (size_t)row * DM + cg * 160 + t * 8;
#pragma unroll
            for (int i = 0; i < 5; ++i) {
                const uint4 q = ldg_nc(xp + i * 32);
                x1[4 * i] = q.x; x1[4 * i + 1] = q.y; x1[4 * i + 2] = q.z; x1[4 * i + 3] = q.w;
            }
            uint4 af[20];
            const uint4* gi = &S.g_o[(size_t)((((ep & 1) * 32 + rb64) * 4 + w) * 40 + wg * 20) * 32 + lane];
#pragma unroll
            for (int u = 0; u < 20; ++u) af[u] = ld_b128(gi + u * 32);
            float acc[80];
            const uint64_t d0 = mkdesc(sb + OFF_RING + wg * 8 * WOSTEP_B, 2560, 128), d1 = mkdesc(sb + OFF_KV + wg * 6 * WOSTEP_B, 2560, 128);
#pragma unroll
            for (int u = 0; u < 20; ++u) {
                if (u == 0 || u == 8 || u == 14 || u == 17) mbar_wait(BAR(B_WO + wg * 4 + (u == 0 ? 0 : u == 8 ? 1 : u == 14 ? 2 : 3)), 0);
                if (u % 5 == 0) {
                    uint32_t it = 0;
                    while (__any_sync(~0u, !(af[u].x && af[u + 1].x && af[u + 2].x && af[u + 3].x && af[u + 4].x)) && ++it < SPIN_MAX) {
#pragma unroll
                        for (int i = 0; i < 5; ++i) af[u + i] = ld_b128(gi + (u + i) * 32);
                    }
                    if (u == 0) TS(10);
                }
                if (u % 5 == 0 || u == 8 || u == 14 || u == 17) WG_FENCE();
                const uint64_t d = u < 8 ? d0 + (uint64_t)((u * WOSTEP_B) >> 4)
                                         : d1 + (uint64_t)((u < 14 ? (u - 8) * WOSTEP_B : KVR + (u - 14) * WOSTEP_B) >> 4);
                if (u == 0) wgmma_n160_init(acc, af[u].x, af[u].y, af[u].z, af[u].w, d);
                else wgmma_n160(acc, af[u].x, af[u].y, af[u].z, af[u].w, d);
            }
            WG_COMMIT();
            WG_WAIT(0);
            pin(acc);
            TS(11);
            if (lane == 0) mbar_arrive(BAR(B_WODONE));
            bar_sync(2 + wg, 128);
            float2* snd = reinterpret_cast<float2*>(smem + OFF_RING + wg * 8 * WOSTEP_B) + (tid & 127);
            const float2* rcv = reinterpret_cast<const float2*>(smem + OFF_RING + (1 - wg) * 8 * WOSTEP_B) + (tid & 127);
#pragma unroll
            for (int j = 0; j < 20; ++j) snd[j * 128] = make_float2(acc[4 * j + 2], acc[4 * j + 3]);
            mbar_wait(BAR(B_MOD2), 0);
            bar_sync(6, 256);
#pragma unroll
            for (int i = 0; i < 5; ++i) {
                const uint4 ga = *reinterpret_cast<const uint4*>(smem + OFF_TAB + i * 64 + t * 16);
                const uint32_t gav[4] = {ga.x, ga.y, ga.z, ga.w};
#pragma unroll
                for (int jj = 0; jj < 4; ++jj) {
                    const int j = 4 * i + jj;
                    const float2 q = rcv[j * 128];
                    x1[j] = hadd2_bf16(x1[j], hmul2_bf16(gav[jj], pack_bf16(acc[4 * j] + q.x, acc[4 * j + 1] + q.y)));
                }
            }
        }
        LnCoef lc;
        uint32_t key;
        {
            float z[4] = {0.f, 0.f, 0.f, 0.f}, qa[4] = {0.f, 0.f, 0.f, 0.f}, qb[4] = {0.f, 0.f, 0.f, 0.f};
#pragma unroll
            for (int i = 0; i < 5; ++i) {
                const uint2 bw = *reinterpret_cast<const uint2*>(smem + OFF_TABW + i * 256 + lane * 8);
                const uint32_t wq[4] = {x1[4 * i], x1[4 * i + 1], x1[4 * i + 2], x1[4 * i + 3]};
                mma16816(z, wq, bw.x, bw.y);
                mma1688(qa, wq[0], wq[1], wq[0]); mma1688(qb, wq[0], wq[1], wq[1]);
                mma1688(qa, wq[2], wq[3], wq[2]); mma1688(qb, wq[2], wq[3], wq[3]);
            }
            const float s2 = __shfl_sync(~0u, (g & 1) ? qa[1] + qb[3] : qa[0] + qb[2], (lane & ~3) + (g >> 1));
            uint4* sp = &S.g_stat[row * 8 + t * 2];
            st_ll8(reinterpret_cast<uint2*>(sp) + cg, __float_as_uint(t == 3 ? s2 : z[0] + z[3]), ep);
            TS(12);
            uint4 pa, pb;
            uint32_t it = 0;
            do { pa = ld_ll16(sp); pb = ld_ll16(sp + 1); } while (!(pa.y == ep && pa.w == ep && pb.y == ep && pb.w == ep) && ++it < SPIN_MAX);
            const float s = (__uint_as_float(pa.x) + __uint_as_float(pa.z)) + (__uint_as_float(pb.x) + __uint_as_float(pb.z));
            const float mean = __shfl_sync(~0u, s, lane & ~3) * (1.0f / DM);
            const float s3 = __shfl_sync(~0u, s, (lane & ~3) + 1) + __shfl_sync(~0u, s, (lane & ~3) + 2);
            const float rstd = rsqrtf(fmaxf(__shfl_sync(~0u, s, lane | 3) * (1.0f / DM) - mean * mean, 0.f) + 1e-5f);
            lc = ln_coef(mean, rstd);
            const float2 cc = *reinterpret_cast<const float2*>(smem + OFF_CONST);
            const uint32_t rb_ = __float_as_uint(rstd * (s3 - mean * cc.x) + cc.y);
            key = (((rb_ & 0x80000000u) ? ~rb_ : (rb_ | 0x80000000u)) & 0xFFFFF800u) | (uint32_t)(2047 - row);
        }
        TS(13);
        uint32_t lk1, lk2;
        {
            const uint32_t k1 = __reduce_max_sync(~0u, key);
            const uint32_t k2 = __reduce_max_sync(~0u, key == k1 ? 0u : key);
            uint32_t* cand = reinterpret_cast<uint32_t*>(smem + OFF_CAND);
            if (lane == 0) *reinterpret_cast<uint2*>(cand + 2 * warp) = make_uint2(k1, k2);
            bar_sync(6, 256);
            const uint32_t kk = cand[lane & 15];
            lk1 = __reduce_max_sync(~0u, kk);
            lk2 = __reduce_max_sync(~0u, kk == lk1 ? 0u : kk);
            if (cg == 0 && tid == 0) st_ll16(&S.g_cand[rb64 * 8], lk1, lk2, ep);
        }
        uint4* outp = reinterpret_cast<uint4*>(P.out + (size_t)row * DM + cg * 160) + t;
        const bool lcand = key == lk1 || key == lk2;
        uint32_t ov[20];
        {
            uint32_t h2[20];
#pragma unroll
            for (int i = 0; i < 5; ++i) {
                const uint4 c1 = *reinterpret_cast<const uint4*>(smem + OFF_TAB + 320 + i * 64 + t * 16);
                const uint4 sh = *reinterpret_cast<const uint4*>(smem + OFF_TAB + 640 + i * 64 + t * 16);
                h2[4 * i] = hfma2_bf16(ln_apply(x1[4 * i], lc), c1.x, sh.x);
                h2[4 * i + 1] = hfma2_bf16(ln_apply(x1[4 * i + 1], lc), c1.y, sh.y);
                h2[4 * i + 2] = hfma2_bf16(ln_apply(x1[4 * i + 2], lc), c1.z, sh.z);
                h2[4 * i + 3] = hfma2_bf16(ln_apply(x1[4 * i + 3], lc), c1.w, sh.w);
            }
            if (lcand) {
                uint4* rp = &S.g_row[(rb64 * 2 + (key == lk1 ? 0 : 1)) * 320 + cg * 40 + 2 * t];
#pragma unroll
                for (int j = 0; j < 10; ++j) st_ll16(rp + (j >> 1) * 8 + (j & 1), h2[2 * j], h2[2 * j + 1], ep);
#pragma unroll
                for (int j = 0; j < 10; ++j) st_ll16(rp + 160 + (j >> 1) * 8 + (j & 1), x1[2 * j], x1[2 * j + 1], ep);
            }
#pragma unroll
            for (int i = 0; i < 5; ++i) {
                const uint4 gb = *reinterpret_cast<const uint4*>(smem + OFF_TAB + 960 + i * 64 + t * 16);
                ov[4 * i] = hadd2_bf16(x1[4 * i], hmul2_bf16(gb.x, h2[4 * i]));
                ov[4 * i + 1] = hadd2_bf16(x1[4 * i + 1], hmul2_bf16(gb.y, h2[4 * i + 1]));
                ov[4 * i + 2] = hadd2_bf16(x1[4 * i + 2], hmul2_bf16(gb.z, h2[4 * i + 2]));
                ov[4 * i + 3] = hadd2_bf16(x1[4 * i + 3], hmul2_bf16(gb.w, h2[4 * i + 3]));
                if (!lcand) outp[4 * i] = make_uint4(ov[4 * i], ov[4 * i + 1], ov[4 * i + 2], ov[4 * i + 3]);
            }
        }
        TS(14);
        const uint32_t ldoff = (((lane >> 1) & 3) * 4 + (lane >> 4) * 2 + (lane & 1)) * 32 + ((((lane >> 3) ^ (lane >> 1)) & 1) << 4);
        uint32_t wa[12][4];
        if (bid < 96) {
            mbar_wait(BAR(B_GU), 0);
#pragma unroll
            for (int i = 0; i < 5; ++i) {
                ldmatrix4_t(wa[i], sb + OFF_GU + (warp * 5 + i) * 512 + ldoff);
                ldmatrix4_t(wa[5 + i], sb + OFF_GU + 20480 + (warp * 5 + i) * 512 + ldoff);
            }
        }
        mbar_wait(BAR(B_TOP), 0);
        TS(15);
        const uint2 top = *reinterpret_cast<const uint2*>(smem + OFF_CAND + 64);
        const int row0 = 2047 - (int)(top.x & 2047u), row1 = 2047 - (int)(top.y & 2047u);
        const int slot0 = (row0 >> 6) * 2, slot1 = (row1 >> 6) * 2 + ((row0 >> 6) == (row1 >> 6) ? 1 : 0);
        float* red = reinterpret_cast<float*>(smem + OFF_RED);
        if (bid < 96) {
            uint4 bf[5];
            const uint4* hp = &S.g_row[((g & 1) ? slot1 : slot0) * 320 + warp * 20 + t];
            uint32_t it = 0;
            bool ok;
            do {
                ok = true;
#pragma unroll
                for (int i = 0; i < 5; ++i) { bf[i] = ld_ll16(hp + 4 * i); ok = ok && bf[i].y == ep && bf[i].w == ep; }
            } while (!ok && ++it < SPIN_MAX);
            __syncwarp();
            float cgt[4] = {0.f, 0.f, 0.f, 0.f}, cup[4] = {0.f, 0.f, 0.f, 0.f};
#pragma unroll
            for (int i = 0; i < 5; ++i) { mma16816(cgt, wa[i], bf[i].x, bf[i].z); mma16816(cup, wa[5 + i], bf[i].x, bf[i].z); }
            float* rp = red + warp * 64 + (t & 1) * 16 + (t >> 1) * 8 + g;
            rp[0] = t == 0 ? cgt[0] : t == 1 ? cgt[1] : t == 2 ? cgt[2] : cgt[3];
            rp[32] = t == 0 ? cup[0] : t == 1 ? cup[1] : t == 2 ? cup[2] : cup[3];
            bar_sync(6, 256);
            if (warp == 0) {
                float gs = 0.f, us = 0.f;
#pragma unroll
                for (int i = 0; i < 8; ++i) { gs += red[i * 64 + lane]; us += red[i * 64 + 32 + lane]; }
                gs = rbf(gs); us = rbf(us);
                const float av = rbf(gs * sigmoidf_(gs)) * us;
                const float hi = __shfl_down_sync(~0u, av, 1);
                if (!(lane & 1)) st_ll8(reinterpret_cast<uint2*>(S.g_act) + bid * 16 + (lane >> 1), pack_bf16(av, hi), ep);
            }
        }
        TS(16);
        if (lcand && key != top.x && key != top.y) {
#pragma unroll
            for (int i = 0; i < 5; ++i) outp[4 * i] = make_uint4(ov[4 * i], ov[4 * i + 1], ov[4 * i + 2], ov[4 * i + 3]);
        }
        if (bid >= 88) {
            mbar_wait(BAR(B_DN), 0);
#pragma unroll
            for (int i = 0; i < 12; ++i) ldmatrix4_t(wa[i], sb + OFF_DN + (warp * 12 + i) * 512 + ldoff);
            uint2 fh, fx;
            uint32_t it = 0;
            {
                const uint2* fp = reinterpret_cast<const uint2*>(&S.g_row[((lane >> 4) ? slot1 : slot0) * 320]) + (bid - 88) * 8 + ((lane & 15) >> 1);
                do { fh = ld_ll8(fp); fx = ld_ll8(fp + 320); } while (!(fh.y == ep && fx.y == ep) && ++it < SPIN_MAX);
            }
            uint4 bf[12];
            const uint4* ap = &S.g_act[warp * 96 + (lane & 7)];
            bool ok;
            do {
                ok = true;
#pragma unroll
                for (int i = 0; i < 12; ++i) { bf[i] = ld_ll16(ap + 8 * i); ok = ok && bf[i].y == ep && bf[i].w == ep; }
            } while (!ok && ++it < SPIN_MAX);
            __syncwarp();
            TS(17);
            float c0[4] = {0.f, 0.f, 0.f, 0.f}, c1[4] = {0.f, 0.f, 0.f, 0.f};
#pragma unroll
            for (int i = 0; i < 6; ++i) { mma16816(c0, wa[2 * i], bf[2 * i].x, bf[2 * i].z); mma16816(c1, wa[2 * i + 1], bf[2 * i + 1].x, bf[2 * i + 1].z); }
            float* rp = red + 512 + warp * 32 + (t & 1) * 16 + (t >> 1) * 8 + g;
            rp[0] = t == 0 ? c0[0] + c1[0] : t == 1 ? c0[1] + c1[1] : t == 2 ? c0[2] + c1[2] : c0[3] + c1[3];
            bar_sync(6, 256);
            if (warp == 0) {
                float y = 0.f;
#pragma unroll
                for (int i = 0; i < 8; ++i) y += red[512 + i * 32 + lane];
                const uint32_t ku = ((lane >> 4) ? top.y : top.x) & 0xFFFFF800u;
                const float r = rbf(__uint_as_float((ku & 0x80000000u) ? (ku & 0x7FFFFFFFu) | 0x400u : ~(ku | 0x400u)));
                const float y2 = rbf(rbf(y) * rbf(sigmoidf_(r)));
                const float h2 = (lane & 1) ? bf_hi(fh.x) : bf_lo(fh.x), xx = (lane & 1) ? bf_hi(fx.x) : bf_lo(fx.x);
                const float gbv = reinterpret_cast<const float*>(smem + OFF_GBD)[lane & 15];
                P.out[(size_t)((lane >> 4) ? row1 : row0) * DM + (bid - 88) * 16 + (lane & 15)] = __float2bfloat16_rn(xx + rbf(gbv * rbf(h2 + y2)));
            }
        }
        TS(18);
    }
}

}

typedef CUresult (*EncodeFn)(CUtensorMap*, CUtensorMapDataType, cuuint32_t, void*, const cuuint64_t*, const cuuint64_t*, const cuuint32_t*,
                             const cuuint32_t*, CUtensorMapInterleave, CUtensorMapSwizzle, CUtensorMapL2promotion, CUtensorMapFloatOOBfill);

extern "C" void kernel_launch(void* const* d_in, const int* in_sizes, int n_in, void* d_out, int out_size) {
    (void)in_sizes; (void)n_in; (void)out_size;
    static EncodeFn enc = nullptr;
    static void* scratch = nullptr;
    if (!enc) {
        void* fn = nullptr;
        cudaDriverEntryPointQueryResult qr;
        cudaGetDriverEntryPoint("cuTensorMapEncodeTiled", &fn, cudaEnableDefault, &qr);
        enc = (EncodeFn)fn;
        cudaGetSymbolAddress(&scratch, g_scratch);
        cudaFuncSetAttribute(fused_kernel, cudaFuncAttributeMaxDynamicSharedMemorySize, SMEM_BYTES);
    }
    Params P;
    P.x = (const __nv_bfloat16*)d_in[0];
    P.wqkv = (const __nv_bfloat16*)d_in[1];
    P.wo = (const __nv_bfloat16*)d_in[2];
    P.wr = (const __nv_bfloat16*)d_in[4];
    P.c = (const __nv_bfloat16*)d_in[8];
    P.wmod = (const __nv_bfloat16*)d_in[9];
    P.out = (__nv_bfloat16*)d_out;
    P.s = (Scratch*)scratch;
    Maps M;
    const cuuint32_t es[2] = {1, 1};
    auto mk = [&](CUtensorMap* m, void* p, cuuint64_t cols, cuuint64_t rows, cuuint32_t bc, cuuint32_t br, CUtensorMapSwizzle sw) {
        const cuuint64_t gd[2] = {cols, rows}, gs[1] = {cols * 2};
        const cuuint32_t bx[2] = {bc, br};
        enc(m, CU_TENSOR_MAP_DATA_TYPE_BFLOAT16, 2, p, gd, gs, bx, es, CU_TENSOR_MAP_INTERLEAVE_NONE, sw,
            CU_TENSOR_MAP_L2_PROMOTION_L2_256B, CU_TENSOR_MAP_FLOAT_OOB_FILL_NONE);
    };
    mk(&M.x, d_in[0], DM, SEQ, 64, 128, CU_TENSOR_MAP_SWIZZLE_128B);
    mk(&M.m, d_in[9], 6 * DM, DM, 32, 80, CU_TENSOR_MAP_SWIZZLE_NONE);
    mk(&M.w[0], d_in[5], FF, DM, 16, 128, CU_TENSOR_MAP_SWIZZLE_32B);
    mk(&M.w[1], d_in[6], FF, DM, 16, 128, CU_TENSOR_MAP_SWIZZLE_32B);
    mk(&M.w[2], d_in[7], DM, FF, 16, 128, CU_TENSOR_MAP_SWIZZLE_32B);
    fused_kernel<<<NCTA, NTHR, SMEM_BYTES, cudaStreamPerThread>>>(P, M);
}
```

```cpp
#include <cuda_runtime.h>
#include <cuda.h>
#include <cuda_bf16.h>
#include <stdint.h>

namespace {

constexpr int SEQ = 2048, DM = 640, FF = 1536;
constexpr int NCTA = 128, NTHR = 384;

constexpr int NSLOT = 4, CHUNK_B = 20480;
constexpr int OFF_RING = 0;
constexpr int KP = 5120, VP = 6144, KVH = KP + VP;
constexpr int KVR = 6 * KVH;
constexpr int OFF_KV = NSLOT * CHUNK_B;
constexpr int OFF_MISC = OFF_KV + 2 * KVR;
constexpr int OFF_X = OFF_MISC - 10 * 16384;
constexpr int OFF_MT = OFF_MISC;
constexpr int OFF_STG = OFF_MISC;
constexpr int OFF_TAB = OFF_MT + 8192;
constexpr int OFF_TABW = OFF_TAB + 1280;
constexpr int OFF_GBD = OFF_TABW + 1280;
constexpr int OFF_CONST = OFF_GBD + 64;
constexpr int OFF_RED = OFF_CONST + 16;
constexpr int OFF_RED2 = OFF_RED + 3072;
constexpr int OFF_CAND = OFF_RED2 + 128;
constexpr int OFF_BAR = OFF_CAND + 96;
constexpr int SMEM_BYTES = OFF_BAR + 64 * 8;
static_assert(OFF_BAR % 8 == 0 && OFF_X % 1024 == 0, "align");
static_assert(SMEM_BYTES <= 232448, "smem");
constexpr int WOSTEP_B = 5120;
constexpr int OFF_QST = OFF_RING + 14 * WOSTEP_B;
constexpr int OFF_GU = OFF_KV;
constexpr int OFF_DN = OFF_KV + 40960;

enum {
    B_FULL = 0, B_EMPTY = 4, B_STG = 8  , B_X = 16  , B_WO = 26  , B_KREM = 34, B_VREM, B_KOWN, B_VOWN, B_HP0, B_ATT,
    B_MOD2, B_GU, B_DN, B_TOP, B_KREP, B_XDONE, B_FFN, B_MFREE, B_REM1, B_STAT, B_COUNT
};
static_assert(B_COUNT <= 64, "barriers");

#define VQ_AFTER 9
#define MJ_MAP (bid < 28 ? bid : bid >= 76 ? bid - 48 : -1)
#define VQ_AT 5
#define VQ_PF 0
#define MOD_T0 1000
#define MOD_DT 1000
#define OFF_B 1
#define PP_B 3
#define VDIRECT 0
#define ACT_NS 0
#define LLMODE 0
#define MOD_AT 8
constexpr uint32_t SPIN_MAX = 1u << 17;

struct Scratch {
    alignas(128) uint32_t g_epoch;
    alignas(128) uint4 g_mod1[640];
    alignas(128) uint2 g_mod[1280];
    alignas(128) uint2 g_msum[40];
    alignas(128) uint4 g_wq[8 * 15 * CHUNK_B / 16];
    alignas(128) uint32_t g_wflag[2 * 10 * 16];
    alignas(128) uint4 g_wo[4 * 40 * WOSTEP_B / 16];
    alignas(128) uint32_t g_woflag[2 * 96];
    alignas(128) uint4 g_gu[96 * 40960 / 16];
    alignas(128) uint4 g_dn[40 * 49152 / 16];
    alignas(128) uint4 g_kv[8 * 32 * 2 * KVH / 16];
    alignas(128) uint32_t g_kvflag[8 * 16 * 32];
    alignas(128) uint4 g_o[2 * 32 * 4 * 40 * 32];
    alignas(128) uint4 g_stat[SEQ * 8];
    alignas(128) uint4 g_cand[8 * 32 * 8];
    alignas(128) uint4 g_row[32 * 2 * 320];
    alignas(128) uint4 g_act[96 * 8];
};
__device__ Scratch g_scratch;
#define TSV(i, v) do { } while (0)
#define TW(acc, stmt) do { stmt; } while (0)
#define TS(i) do { } while (0)

__device__ __forceinline__ uint32_t smem_u32(const void* p) { return (uint32_t)__cvta_generic_to_shared(p); }
__device__ __forceinline__ void mbar_init(uint32_t bar, uint32_t cnt) { asm volatile("mbarrier.init.shared.b64 [%0], %1;" ::"r"(bar), "r"(cnt) : "memory"); }
__device__ __forceinline__ void mbar_arrive(uint32_t bar) { asm volatile("mbarrier.arrive.shared.b64 _, [%0];" ::"r"(bar) : "memory"); }
__device__ __forceinline__ void mbar_arrive_tx(uint32_t bar, uint32_t bytes) { asm volatile("mbarrier.arrive.expect_tx.shared.b64 _, [%0], %1;" ::"r"(bar), "r"(bytes) : "memory"); }
__device__ __forceinline__ bool mbar_try(uint32_t bar, uint32_t parity) {
    uint32_t done;
    asm volatile("{\n.reg .pred p;\nmbarrier.try_wait.parity.shared.b64 p, [%1], %2;\nselp.u32 %0, 1, 0, p;\n}" : "=r"(done) : "r"(bar), "r"(parity) : "memory");
    return done;
}
__device__ __forceinline__ void mbar_wait(uint32_t bar, uint32_t parity) {
    if (__builtin_expect(!mbar_try(bar, parity), 0)) {
#pragma unroll 1
        for (uint32_t it = 0; it < SPIN_MAX && !mbar_try(bar, parity); ++it) { }
    }
}
__device__ __forceinline__ void bulk_g2s(uint32_t dst, const void* src, uint32_t bytes, uint32_t bar) {
    asm volatile("cp.async.bulk.shared::cluster.global.mbarrier::complete_tx::bytes [%0], [%1], %2, [%3];" ::"r"(dst), "l"(src), "r"(bytes), "r"(bar) : "memory");
}
__device__ __forceinline__ void fence_async_smem() { asm volatile("fence.proxy.async.shared::cta;" ::: "memory"); }
__device__ __forceinline__ void bar_sync(int id, int n) { asm volatile("bar.sync %0, %1;" ::"r"(id), "r"(n) : "memory"); }
__device__ __forceinline__ void bar_arrive(int id, int n) { asm volatile("bar.arrive %0, %1;" ::"r"(id), "r"(n) : "memory"); }
#define WG_FENCE() asm volatile("wgmma.fence.sync.aligned;" ::: "memory")
#define WG_COMMIT() asm volatile("wgmma.commit_group.sync.aligned;" ::: "memory")
#define WG_WAIT(n) asm volatile("wgmma.wait_group.sync.aligned %0;" ::"n"(n) : "memory")
template <int N> __device__ __forceinline__ void pin(float (&d)[N]) {
#pragma unroll
    for (int i = 0; i < N; ++i) asm volatile("" : "+f"(d[i])::"memory");
}
__device__ __forceinline__ constexpr uint64_t mkdesc(uint32_t addr, uint32_t lbo, uint32_t sbo) {
    return (uint64_t)(((addr & 0x3FFFFu) >> 4) | ((lbo >> 4) << 16)) | ((uint64_t)(sbo >> 4) << 32);
}
__device__ __forceinline__ uint32_t pack_bf16(float lo, float hi) {
    uint32_t r; asm("cvt.rn.bf16x2.f32 %0, %1, %2;" : "=r"(r) : "f"(hi), "f"(lo)); return r;
}
__device__ __forceinline__ float bf_lo(uint32_t u) { return __uint_as_float(u << 16); }
__device__ __forceinline__ float bf_hi(uint32_t u) { return __uint_as_float(u & 0xffff0000u); }
__device__ __forceinline__ float rbf(float f) { return __bfloat162float(__float2bfloat16_rn(f)); }
__device__ __forceinline__ uint32_t hfma2_bf16(uint32_t a, uint32_t b, uint32_t c) {
    uint32_t r; asm("fma.rn.bf16x2 %0, %1, %2, %3;" : "=r"(r) : "r"(a), "r"(b), "r"(c)); return r;
}
__device__ __forceinline__ void hfma2_ip(uint32_t& a, uint32_t b, uint32_t c) { asm volatile("fma.rn.bf16x2 %0, %0, %1, %2;" : "+r"(a) : "r"(b), "r"(c)); }
template <int OFF> __device__ __forceinline__ void lds128(uint4& v, uint32_t base) {
    asm volatile("ld.shared.v4.u32 {%0,%1,%2,%3}, [%4+%5];" : "=r"(v.x), "=r"(v.y), "=r"(v.z), "=r"(v.w) : "r"(base), "n"(OFF) : "memory");
}
__device__ __forceinline__ float ex2(float x) { float r; asm("ex2.approx.ftz.f32 %0, %1;" : "=f"(r) : "f"(x)); return r; }
__device__ __forceinline__ uint4 ldg_nc(const void* p) {
    uint4 v; asm volatile("ld.global.nc.L1::no_allocate.v4.u32 {%0,%1,%2,%3}, [%4];" : "=r"(v.x), "=r"(v.y), "=r"(v.z), "=r"(v.w) : "l"(p)); return v;
}
__device__ __forceinline__ uint4 ldg_nc256(const void* p) {
    uint4 v; asm volatile("ld.global.nc.L1::no_allocate.L2::256B.v4.u32 {%0,%1,%2,%3}, [%4];" : "=r"(v.x), "=r"(v.y), "=r"(v.z), "=r"(v.w) : "l"(p)); return v;
}
__device__ __forceinline__ uint2 ld_ll8(const void* p) {
    uint64_t v; asm volatile("ld.relaxed.gpu.global.b64 %0, [%1];" : "=l"(v) : "l"(p) : "memory");
    return make_uint2((uint32_t)v, (uint32_t)(v >> 32));
}
__device__ __forceinline__ uint4 ld_ll16(const void* p) {
    uint64_t a, b; asm volatile("ld.relaxed.gpu.global.v2.b64 {%0,%1}, [%2];" : "=l"(a), "=l"(b) : "l"(p) : "memory");
    return make_uint4((uint32_t)a, (uint32_t)(a >> 32), (uint32_t)b, (uint32_t)(b >> 32));
}
__device__ __forceinline__ void st_ll8(void* p, uint32_t d, uint32_t ep) {
    asm volatile("st.relaxed.gpu.global.b64 [%0], %1;" ::"l"(p), "l"((uint64_t)d | ((uint64_t)ep << 32)) : "memory");
}
__device__ __forceinline__ void st_ll16(void* p, uint32_t d0, uint32_t d1, uint32_t ep) {
    asm volatile("st.relaxed.gpu.global.v2.b64 [%0], {%1,%2};" ::"l"(p), "l"((uint64_t)d0 | ((uint64_t)ep << 32)), "l"((uint64_t)d1 | ((uint64_t)ep << 32)) : "memory");
}
__device__ __forceinline__ uint4 ld_b128(const void* p) {
    uint4 v;
    asm volatile("{\n.reg .b128 r;\nld.relaxed.gpu.global.b128 r, [%4];\nmov.b128 {%0,%1,%2,%3}, r;\n}" : "=r"(v.x), "=r"(v.y), "=r"(v.z), "=r"(v.w) : "l"(p) : "memory");
    return v;
}
__device__ __forceinline__ void st_b128(void* p, uint32_t a, uint32_t b, uint32_t c, uint32_t d) {
    asm volatile("{\n.reg .b128 r;\nmov.b128 r, {%1,%2,%3,%4};\nst.relaxed.gpu.global.b128 [%0], r;\n}" ::"l"(p), "r"(a), "r"(b), "r"(c), "r"(d) : "memory");
}
__device__ __forceinline__ void st_flag(void* p, uint32_t ep) { asm volatile("st.relaxed.gpu.global.u32 [%0], %1;" ::"l"(p), "r"(ep) : "memory"); }
__device__ __forceinline__ void stmatrix4(uint32_t addr, uint32_t r0, uint32_t r1, uint32_t r2, uint32_t r3) {
    asm volatile("stmatrix.sync.aligned.m8n8.x4.shared.b16 [%0], {%1,%2,%3,%4};" ::"r"(addr), "r"(r0), "r"(r1), "r"(r2), "r"(r3) : "memory");
}
__device__ __forceinline__ void ldmatrix4_t(uint32_t (&r)[4], uint32_t addr) {
    asm volatile("ldmatrix.sync.aligned.m8n8.x4.trans.shared.b16 {%0,%1,%2,%3}, [%4];" : "=r"(r[0]), "=r"(r[1]), "=r"(r[2]), "=r"(r[3]) : "r"(addr) : "memory");
}
__device__ __forceinline__ void mma16816(float (&c)[4], const uint32_t (&a)[4], uint32_t b0, uint32_t b1) {
    asm volatile("mma.sync.aligned.m16n8k16.row.col.f32.bf16.bf16.f32 {%0,%1,%2,%3}, {%4,%5,%6,%7}, {%8,%9}, {%0,%1,%2,%3};"
                 : "+f"(c[0]), "+f"(c[1]), "+f"(c[2]), "+f"(c[3]) : "r"(a[0]), "r"(a[1]), "r"(a[2]), "r"(a[3]), "r"(b0), "r"(b1));
}
__device__ __forceinline__ void mma1688(float (&c)[4], uint32_t a0, uint32_t a1, uint32_t b0) {
    asm volatile("mma.sync.aligned.m16n8k8.row.col.f32.bf16.bf16.f32 {%0,%1,%2,%3}, {%4,%5}, {%6}, {%0,%1,%2,%3};"
                 : "+f"(c[0]), "+f"(c[1]), "+f"(c[2]), "+f"(c[3]) : "r"(a0), "r"(a1), "r"(b0));
}
__device__ __forceinline__ float rcp(float x) { float r; asm("rcp.approx.ftz.f32 %0, %1;" : "=f"(r) : "f"(x)); return r; }
__device__ __forceinline__ float sigmoidf_(float x) { return rcp(1.0f + ex2(x * -1.4426950408889634f)); }
__device__ __forceinline__ uint32_t hmul2_bf16(uint32_t a, uint32_t b) { uint32_t r; asm("mul.rn.bf16x2 %0, %1, %2;" : "=r"(r) : "r"(a), "r"(b)); return r; }
__device__ __forceinline__ uint32_t hadd2_bf16(uint32_t a, uint32_t b) { uint32_t r; asm("add.rn.bf16x2 %0, %1, %2;" : "=r"(r) : "r"(a), "r"(b)); return r; }
struct LnCoef { uint32_t rh, rl, nm; };
__device__ __forceinline__ LnCoef ln_coef(float mean, float rstd) {
    LnCoef c;
    c.rh = pack_bf16(rstd, rstd);
    const float l = rstd - bf_lo(c.rh), n = -mean * rstd;
    c.rl = pack_bf16(l, l);
    c.nm = pack_bf16(n, n);
    return c;
}
__device__ __forceinline__ uint32_t ln_apply(uint32_t x, const LnCoef& c) { return hfma2_bf16(x, c.rh, hfma2_bf16(x, c.rl, c.nm)); }

__device__ __forceinline__ void bulk_s2g(void* dst, uint32_t src, uint32_t bytes) {
    asm volatile("cp.async.bulk.global.shared::cta.bulk_group [%0], [%1], %2;" ::"l"(dst), "r"(src), "r"(bytes) : "memory");
}
__device__ __forceinline__ void tma_2d(uint32_t dst, const void* map, int c0, int c1, uint32_t bar) {
    asm volatile("cp.async.bulk.tensor.2d.shared::cluster.global.mbarrier::complete_tx::bytes [%0], [%1, {%3,%4}], [%2];"
                 ::"r"(dst), "l"(map), "r"(bar), "r"(c0), "r"(c1) : "memory");
}
__device__ __forceinline__ void ldmatrix4(uint32_t& r0, uint32_t& r1, uint32_t& r2, uint32_t& r3, uint32_t addr) {
    asm volatile("ldmatrix.sync.aligned.m8n8.x4.shared.b16 {%0,%1,%2,%3}, [%4];" : "=r"(r0), "=r"(r1), "=r"(r2), "=r"(r3) : "r"(addr) : "memory");
}
__device__ __forceinline__ uint32_t ld_flag(const void* p) {
    uint32_t v; asm volatile("ld.relaxed.gpu.global.u32 %0, [%1];" : "=r"(v) : "l"(p) : "memory"); return v;
}
__device__ __forceinline__ void fma8(float (&acc)[8], float s, const uint4& v) {
    acc[0] += s * bf_lo(v.x); acc[1] += s * bf_hi(v.x); acc[2] += s * bf_lo(v.y); acc[3] += s * bf_hi(v.y);
    acc[4] += s * bf_lo(v.z); acc[5] += s * bf_hi(v.z); acc[6] += s * bf_lo(v.w); acc[7] += s * bf_hi(v.w);
}
__device__ __forceinline__ float treduce8(const float (&acc)[8], int lane) {
    const bool u1 = lane & 4, u2 = lane & 8, u3 = lane & 16;
    float b4[4], b2[2];
#pragma unroll
    for (int i = 0; i < 4; ++i) { const float snd = u1 ? acc[i] : acc[i + 4], kp = u1 ? acc[i + 4] : acc[i]; b4[i] = kp + __shfl_xor_sync(~0u, snd, 4); }
#pragma unroll
    for (int i = 0; i < 2; ++i) { const float snd = u2 ? b4[i] : b4[i + 2], kp = u2 ? b4[i + 2] : b4[i]; b2[i] = kp + __shfl_xor_sync(~0u, snd, 8); }
    const float snd = u3 ? b2[0] : b2[1], kp = u3 ? b2[1] : b2[0];
    return kp + __shfl_xor_sync(~0u, snd, 16);
}
__device__ __forceinline__ float silu_bf(__nv_bfloat16 c) { const float f = __bfloat162float(c); return rbf(f * sigmoidf_(f)); }

__device__ __forceinline__ void wgmma_n80_init(float (&d)[40], uint32_t a0, uint32_t a1, uint32_t a2, uint32_t a3, uint64_t db) {
    asm volatile("wgmma.mma_async.sync.aligned.m64n80k16.f32.bf16.bf16 "
                 "{%0, %1, %2, %3, %4, %5, %6, %7, %8, %9, %10, %11, %12, %13, %14, %15, "
                 "%16, %17, %18, %19, %20, %21, %22, %23, %24, %25, %26, %27, %28, %29, %30, %31, "
                 "%32, %33, %34, %35, %36, %37, %38, %39}, "
                 "{%40,%41,%42,%43}, %44, 0, 1, 1, 1;\n"
                 : "=f"(d[0]), "=f"(d[1]), "=f"(d[2]), "=f"(d[3]), "=f"(d[4]), "=f"(d[5]), "=f"(d[6]), "=f"(d[7]),
                   "=f"(d[8]), "=f"(d[9]), "=f"(d[10]), "=f"(d[11]), "=f"(d[12]), "=f"(d[13]), "=f"(d[14]), "=f"(d[15]),
                   "=f"(d[16]), "=f"(d[17]), "=f"(d[18]), "=f"(d[19]), "=f"(d[20]), "=f"(d[21]), "=f"(d[22]), "=f"(d[23]),
                   "=f"(d[24]), "=f"(d[25]), "=f"(d[26]), "=f"(d[27]), "=f"(d[28]), "=f"(d[29]), "=f"(d[30]), "=f"(d[31]),
                   "=f"(d[32]), "=f"(d[33]), "=f"(d[34]), "=f"(d[35]), "=f"(d[36]), "=f"(d[37]), "=f"(d[38]), "=f"(d[39])
                 : "r"(a0), "r"(a1), "r"(a2), "r"(a3), "l"(db));
}
__device__ __forceinline__ void wgmma_n80(float (&d)[40], uint32_t a0, uint32_t a1, uint32_t a2, uint32_t a3, uint64_t db) {
    asm volatile("wgmma.mma_async.sync.aligned.m64n80k16.f32.bf16.bf16 "
                 "{%0, %1, %2, %3, %4, %5, %6, %7, %8, %9, %10, %11, %12, %13, %14, %15, "
                 "%16, %17, %18, %19, %20, %21, %22, %23, %24, %25, %26, %27, %28, %29, %30, %31, "
                 "%32, %33, %34, %35, %36, %37, %38, %39}, "
                 "{%40,%41,%42,%43}, %44, 1, 1, 1, 1;\n"
                 : "+f"(d[0]), "+f"(d[1]), "+f"(d[2]), "+f"(d[3]), "+f"(d[4]), "+f"(d[5]), "+f"(d[6]), "+f"(d[7]),
                   "+f"(d[8]), "+f"(d[9]), "+f"(d[10]), "+f"(d[11]), "+f"(d[12]), "+f"(d[13]), "+f"(d[14]), "+f"(d[15]),
                   "+f"(d[16]), "+f"(d[17]), "+f"(d[18]), "+f"(d[19]), "+f"(d[20]), "+f"(d[21]), "+f"(d[22]), "+f"(d[23]),
                   "+f"(d[24]), "+f"(d[25]), "+f"(d[26]), "+f"(d[27]), "+f"(d[28]), "+f"(d[29]), "+f"(d[30]), "+f"(d[31]),
                   "+f"(d[32]), "+f"(d[33]), "+f"(d[34]), "+f"(d[35]), "+f"(d[36]), "+f"(d[37]), "+f"(d[38]), "+f"(d[39])
                 : "r"(a0), "r"(a1), "r"(a2), "r"(a3), "l"(db));
}
__device__ __forceinline__ void wgmma_n64_init(float (&d)[32], uint32_t a0, uint32_t a1, uint32_t a2, uint32_t a3, uint64_t db) {
    asm volatile("wgmma.mma_async.sync.aligned.m64n64k16.f32.bf16.bf16 "
                 "{%0, %1, %2, %3, %4, %5, %6, %7, %8, %9, %10, %11, %12, %13, %14, %15, "
                 "%16, %17, %18, %19, %20, %21, %22, %23, %24, %25, %26, %27, %28, %29, %30, %31}, "
                 "{%32,%33,%34,%35}, %36, 0, 1, 1, 0;\n"
                 : "=f"(d[0]), "=f"(d[1]), "=f"(d[2]), "=f"(d[3]), "=f"(d[4]), "=f"(d[5]), "=f"(d[6]), "=f"(d[7]),
                   "=f"(d[8]), "=f"(d[9]), "=f"(d[10]), "=f"(d[11]), "=f"(d[12]), "=f"(d[13]), "=f"(d[14]), "=f"(d[15]),
                   "=f"(d[16]), "=f"(d[17]), "=f"(d[18]), "=f"(d[19]), "=f"(d[20]), "=f"(d[21]), "=f"(d[22]), "=f"(d[23]),
                   "=f"(d[24]), "=f"(d[25]), "=f"(d[26]), "=f"(d[27]), "=f"(d[28]), "=f"(d[29]), "=f"(d[30]), "=f"(d[31])
                 : "r"(a0), "r"(a1), "r"(a2), "r"(a3), "l"(db));
}
__device__ __forceinline__ void wgmma_n64(float (&d)[32], uint32_t a0, uint32_t a1, uint32_t a2, uint32_t a3, uint64_t db) {
    asm volatile("wgmma.mma_async.sync.aligned.m64n64k16.f32.bf16.bf16 "
                 "{%0, %1, %2, %3, %4, %5, %6, %7, %8, %9, %10, %11, %12, %13, %14, %15, "
                 "%16, %17, %18, %19, %20, %21, %22, %23, %24, %25, %26, %27, %28, %29, %30, %31}, "
                 "{%32,%33,%34,%35}, %36, 1, 1, 1, 0;\n"
                 : "+f"(d[0]), "+f"(d[1]), "+f"(d[2]), "+f"(d[3]), "+f"(d[4]), "+f"(d[5]), "+f"(d[6]), "+f"(d[7]),
                   "+f"(d[8]), "+f"(d[9]), "+f"(d[10]), "+f"(d[11]), "+f"(d[12]), "+f"(d[13]), "+f"(d[14]), "+f"(d[15]),
                   "+f"(d[16]), "+f"(d[17]), "+f"(d[18]), "+f"(d[19]), "+f"(d[20]), "+f"(d[21]), "+f"(d[22]), "+f"(d[23]),
                   "+f"(d[24]), "+f"(d[25]), "+f"(d[26]), "+f"(d[27]), "+f"(d[28]), "+f"(d[29]), "+f"(d[30]), "+f"(d[31])
                 : "r"(a0), "r"(a1), "r"(a2), "r"(a3), "l"(db));
}
__device__ __forceinline__ void wgmma_n24_init(float (&d)[12], uint32_t a0, uint32_t a1, uint32_t a2, uint32_t a3, uint64_t db) {
    asm volatile("wgmma.mma_async.sync.aligned.m64n24k16.f32.bf16.bf16 "
                 "{%0, %1, %2, %3, %4, %5, %6, %7, %8, %9, %10, %11}, "
                 "{%12,%13,%14,%15}, %16, 0, 1, 1, 1;\n"
                 : "=f"(d[0]), "=f"(d[1]), "=f"(d[2]), "=f"(d[3]), "=f"(d[4]), "=f"(d[5]), "=f"(d[6]), "=f"(d[7]),
                   "=f"(d[8]), "=f"(d[9]), "=f"(d[10]), "=f"(d[11])
                 : "r"(a0), "r"(a1), "r"(a2), "r"(a3), "l"(db));
}
__device__ __forceinline__ void wgmma_n24(float (&d)[12], uint32_t a0, uint32_t a1, uint32_t a2, uint32_t a3, uint64_t db) {
    asm volatile("wgmma.mma_async.sync.aligned.m64n24k16.f32.bf16.bf16 "
                 "{%0, %1, %2, %3, %4, %5, %6, %7, %8, %9, %10, %11}, "
                 "{%12,%13,%14,%15}, %16, 1, 1, 1, 1;\n"
                 : "+f"(d[0]), "+f"(d[1]), "+f"(d[2]), "+f"(d[3]), "+f"(d[4]), "+f"(d[5]), "+f"(d[6]), "+f"(d[7]),
                   "+f"(d[8]), "+f"(d[9]), "+f"(d[10]), "+f"(d[11])
                 : "r"(a0), "r"(a1), "r"(a2), "r"(a3), "l"(db));
}
__device__ __forceinline__ void wgmma_n160_init(float (&d)[80], uint32_t a0, uint32_t a1, uint32_t a2, uint32_t a3, uint64_t db) {
    asm volatile("wgmma.mma_async.sync.aligned.m64n160k16.f32.bf16.bf16 "
                 "{%0, %1, %2, %3, %4, %5, %6, %7, %8, %9, %10, %11, %12, %13, %14, %15, "
                 "%16, %17, %18, %19, %20, %21, %22, %23, %24, %25, %26, %27, %28, %29, %30, %31, "
                 "%32, %33, %34, %35, %36, %37, %38, %39, %40, %41, %42, %43, %44, %45, %46, %47, "
                 "%48, %49, %50, %51, %52, %53, %54, %55, %56, %57, %58, %59, %60, %61, %62, %63, "
                 "%64, %65, %66, %67, %68, %69, %70, %71, %72, %73, %74, %75, %76, %77, %78, %79}, "
                 "{%80,%81,%82,%83}, %84, 0, 1, 1, 1;\n"
                 : "=f"(d[0]), "=f"(d[1]), "=f"(d[2]), "=f"(d[3]), "=f"(d[4]), "=f"(d[5]), "=f"(d[6]), "=f"(d[7]),
                   "=f"(d[8]), "=f"(d[9]), "=f"(d[10]), "=f"(d[11]), "=f"(d[12]), "=f"(d[13]), "=f"(d[14]), "=f"(d[15]),
                   "=f"(d[16]), "=f"(d[17]), "=f"(d[18]), "=f"(d[19]), "=f"(d[20]), "=f"(d[21]), "=f"(d[22]), "=f"(d[23]),
                   "=f"(d[24]), "=f"(d[25]), "=f"(d[26]), "=f"(d[27]), "=f"(d[28]), "=f"(d[29]), "=f"(d[30]), "=f"(d[31]),
                   "=f"(d[32]), "=f"(d[33]), "=f"(d[34]), "=f"(d[35]), "=f"(d[36]), "=f"(d[37]), "=f"(d[38]), "=f"(d[39]),
                   "=f"(d[40]), "=f"(d[41]), "=f"(d[42]), "=f"(d[43]), "=f"(d[44]), "=f"(d[45]), "=f"(d[46]), "=f"(d[47]),
                   "=f"(d[48]), "=f"(d[49]), "=f"(d[50]), "=f"(d[51]), "=f"(d[52]), "=f"(d[53]), "=f"(d[54]), "=f"(d[55]),
                   "=f"(d[56]), "=f"(d[57]), "=f"(d[58]), "=f"(d[59]), "=f"(d[60]), "=f"(d[61]), "=f"(d[62]), "=f"(d[63]),
                   "=f"(d[64]), "=f"(d[65]), "=f"(d[66]), "=f"(d[67]), "=f"(d[68]), "=f"(d[69]), "=f"(d[70]), "=f"(d[71]),
                   "=f"(d[72]), "=f"(d[73]), "=f"(d[74]), "=f"(d[75]), "=f"(d[76]), "=f"(d[77]), "=f"(d[78]), "=f"(d[79])
                 : "r"(a0), "r"(a1), "r"(a2), "r"(a3), "l"(db));
}
__device__ __forceinline__ void wgmma_n160(float (&d)[80], uint32_t a0, uint32_t a1, uint32_t a2, uint32_t a3, uint64_t db) {
    asm volatile("wgmma.mma_async.sync.aligned.m64n160k16.f32.bf16.bf16 "
                 "{%0, %1, %2, %3, %4, %5, %6, %7, %8, %9, %10, %11, %12, %13, %14, %15, "
                 "%16, %17, %18, %19, %20, %21, %22, %23, %24, %25, %26, %27, %28, %29, %30, %31, "
                 "%32, %33, %34, %35, %36, %37, %38, %39, %40, %41, %42, %43, %44, %45, %46, %47, "
                 "%48, %49, %50, %51, %52, %53, %54, %55, %56, %57, %58, %59, %60, %61, %62, %63, "
                 "%64, %65, %66, %67, %68, %69, %70, %71, %72, %73, %74, %75, %76, %77, %78, %79}, "
                 "{%80,%81,%82,%83}, %84, 1, 1, 1, 1;\n"
                 : "+f"(d[0]), "+f"(d[1]), "+f"(d[2]), "+f"(d[3]), "+f"(d[4]), "+f"(d[5]), "+f"(d[6]), "+f"(d[7]),
                   "+f"(d[8]), "+f"(d[9]), "+f"(d[10]), "+f"(d[11]), "+f"(d[12]), "+f"(d[13]), "+f"(d[14]), "+f"(d[15]),
                   "+f"(d[16]), "+f"(d[17]), "+f"(d[18]), "+f"(d[19]), "+f"(d[20]), "+f"(d[21]), "+f"(d[22]), "+f"(d[23]),
                   "+f"(d[24]), "+f"(d[25]), "+f"(d[26]), "+f"(d[27]), "+f"(d[28]), "+f"(d[29]), "+f"(d[30]), "+f"(d[31]),
                   "+f"(d[32]), "+f"(d[33]), "+f"(d[34]), "+f"(d[35]), "+f"(d[36]), "+f"(d[37]), "+f"(d[38]), "+f"(d[39]),
                   "+f"(d[40]), "+f"(d[41]), "+f"(d[42]), "+f"(d[43]), "+f"(d[44]), "+f"(d[45]), "+f"(d[46]), "+f"(d[47]),
                   "+f"(d[48]), "+f"(d[49]), "+f"(d[50]), "+f"(d[51]), "+f"(d[52]), "+f"(d[53]), "+f"(d[54]), "+f"(d[55]),
                   "+f"(d[56]), "+f"(d[57]), "+f"(d[58]), "+f"(d[59]), "+f"(d[60]), "+f"(d[61]), "+f"(d[62]), "+f"(d[63]),
                   "+f"(d[64]), "+f"(d[65]), "+f"(d[66]), "+f"(d[67]), "+f"(d[68]), "+f"(d[69]), "+f"(d[70]), "+f"(d[71]),
                   "+f"(d[72]), "+f"(d[73]), "+f"(d[74]), "+f"(d[75]), "+f"(d[76]), "+f"(d[77]), "+f"(d[78]), "+f"(d[79])
                 : "r"(a0), "r"(a1), "r"(a2), "r"(a3), "l"(db));
}

struct Params {
    const __nv_bfloat16 *wmod, *c, *wqkv, *x;
    Scratch* s;
    const __nv_bfloat16 *wo, *wr;
    __nv_bfloat16* out;
    uint32_t zero;
};
struct Maps { CUtensorMap x, w[3]; };

__global__ void __launch_bounds__(NTHR, 1) fused_kernel(const __grid_constant__ Params P, const __grid_constant__ Maps M) {
    const int tid = threadIdx.x, bid = blockIdx.x, lane = tid & 31;
    const int rp_kc = (bid - 28) / 10, rp_line = (bid - 28) - rp_kc * 10;
    uint4 kr[2], mv[5];
    __nv_bfloat16 cv[5];
    const int mj = MJ_MAP;
    if (tid < 256) {
        if (mj >= 0) {
            const int r0 = (mj & 1) * 320 + (tid >> 2);
            const __nv_bfloat16* s = P.wmod + (size_t)r0 * 3840 + (mj >> 1) * 32 + (tid & 3) * 8;
#pragma unroll
            for (int i = 0; i < 5; ++i) cv[i] = P.c[r0 + i * 64];
#pragma unroll
            for (int i = 0; i < 5; ++i) mv[i] = ldg_nc256(s + (size_t)i * 64 * 3840);
        }
        if (bid >= 28) {
            const __nv_bfloat16* s = P.wqkv + (size_t)(rp_kc * 64 + (tid >> 5) * 8 + (lane >> 3)) * 1920 + 640 + rp_line * 64 + (lane & 7) * 8;
            kr[0] = ldg_nc(s); kr[1] = ldg_nc(s + 4 * 1920);
        }
    }
    Scratch& S = *P.s;
    uint32_t ep;
    extern __shared__ __align__(1024) unsigned char smem[];
    constexpr uint32_t sb = 1024;
    const int warp = __shfl_sync(~0u, tid >> 5, 0);
    const int rb = (bid >> 5) * 4 + ((bid & 15) >> 2);
    const int hg = ((bid >> 4) & 1) * 4 + (bid & 3);
    const int rb64 = rb * 2 + (hg >> 2), cg = hg & 3;
    auto BAR = [&](int i) { return sb + OFF_BAR + i * 8; };
    const int rp_cc = rp_line * 8 + (lane & 7), rp_hh = rp_cc / 10;
    uint4* dq0 = S.g_wq + (size_t)(rp_hh * 240 + rp_kc * 8) * 80 + (rp_cc - rp_hh * 10) * 8;

    if (warp >= 8) {
        asm volatile("setmaxnreg.dec.sync.aligned.u32 40;");
        const int at = tid - 256, aw = warp - 8;
        if (smem_u32(smem) != sb) __trap();
        if (at == 0) {
            asm volatile("prefetch.tensormap [%0];" ::"l"(&M.x) : "memory");
            for (int i = 0; i < 10; ++i) { mbar_init(BAR(B_X + i), 1); mbar_arrive_tx(BAR(B_X + i), 16384); }
            fence_async_smem();
        } else if (at == 32) {
            for (int i = 0; i < NSLOT; ++i) { mbar_init(BAR(B_FULL + i), 1); mbar_init(BAR(B_EMPTY + i), 8); }
            for (int i = 0; i < 8; ++i) mbar_init(BAR(B_WO + i), 1);
            mbar_init(BAR(B_STG), 1); mbar_init(BAR(B_STG + 1), 1);
            mbar_init(BAR(B_KREM), 1); mbar_init(BAR(B_VREM), 2); mbar_init(BAR(B_KOWN), 8);
            mbar_init(BAR(B_VOWN), 8); mbar_init(BAR(B_HP0), 8); mbar_init(BAR(B_ATT), 8); mbar_init(BAR(B_MOD2), 64);
            mbar_init(BAR(B_GU), 1); mbar_init(BAR(B_DN), 1); mbar_init(BAR(B_TOP), 1);
            mbar_init(BAR(B_KREP), 8); mbar_init(BAR(B_XDONE), 8); mbar_init(BAR(B_FFN), 1);
            mbar_init(BAR(B_MFREE), 2); mbar_init(BAR(B_REM1), 2); mbar_init(BAR(B_STAT), 8);
            fence_async_smem();
        }
        if (aw == 0) {
            __syncwarp();
            if (lane < 10) tma_2d(sb + OFF_X + lane * 16384, &M.x, lane * 64, rb * 128, BAR(B_X + lane));
        }
        bar_sync(0, NTHR);
        ep = ld_flag(&S.g_epoch) + 1;
        const int first = rb >= 2 ? 0 : 4 - rb * 2;
        unsigned char* gk = reinterpret_cast<unsigned char*>(S.g_kv) + (ptrdiff_t)(hg * 32 + rb * 2 - 4 + (lane >> 1)) * (2 * KVH);
        const uint32_t sk = sb + OFF_KV + (lane & 1) * KVR + (lane >> 1) * KVH;
        if (aw == 0) {
            if (bid >= 28) {
                mbar_wait(BAR(B_KREP), 0);
                const uint32_t rbk = __reduce_or_sync(~0u, ld_flag(dq0 + (lane >> 3) * 80) | ld_flag(dq0 + (lane >> 3) * 80 + 320));
                if (lane == 0) st_flag(&S.g_wflag[rp_line * 16 + rp_kc], ep | (rbk & P.zero));
            }
            TS(0);
            auto fetch = [&](int kv, int hp) {
                const uint32_t bytes = kv == 0 ? KP : VP, bar = BAR(hp ? B_REM1 : B_KREM + kv);
                if (lane == 0) mbar_arrive_tx(bar, bytes * (4 - first));
                if (lane < 4 && lane >= first) {
                    const uint32_t* fp = &S.g_kvflag[(hg * 16 + rb - 2 + (lane >> 1)) * 32 + kv];
                    uint32_t it = 0;
                    while (!hp && ld_flag(fp) != ep && ++it < SPIN_MAX) { }
                    bulk_g2s(sb + OFF_KV + hp * KVR + lane * KVH + kv * KP,
                             reinterpret_cast<unsigned char*>(S.g_kv) + (ptrdiff_t)(hg * 32 + rb * 2 - 4 + lane) * (2 * KVH) + kv * 2 * KP + hp * bytes, bytes, bar);
                }
                __syncwarp();
            };
            const uint32_t* fl = S.g_wflag + (((hg * 10) >> 3) + (lane >> 4)) * 16 + min(lane & 15, 9);
            const unsigned char* src = reinterpret_cast<const unsigned char*>(S.g_wq) + (size_t)hg * 15 * CHUNK_B;
            uint32_t it = 0;
#pragma unroll 1
            for (int c = 0; c < 15; ++c) {
                if (c == 0 || c == 5) {
                    while (!__all_sync(~0u, ld_flag(fl) == ep) && ++it < SPIN_MAX) { }
                    fl += 160;
                }
                if (c == 0) TS(1);
                if (c >= NSLOT) mbar_wait(BAR(B_EMPTY + (c & 3)), ((c >> 2) - 1) & 1);
                else if (c == 2) mbar_wait(BAR(B_XDONE), 0);
                if (lane == 0) {
                    mbar_arrive_tx(BAR(B_FULL + (c & 3)), CHUNK_B);
                    bulk_g2s(sb + OFF_RING + (c & 3) * CHUNK_B, src, CHUNK_B, BAR(B_FULL + (c & 3)));
                }
                TS(10 + c);
                src += CHUNK_B;
            }
            TS(2);
#pragma unroll 1
            for (int i = 0; i < 4; ++i) {
                if (i == 1) mbar_wait(BAR(B_MFREE), 0);
                fetch(i & 1, i >> 1);
                if (i < 2) TS(6 + i);
            }
            {
                const uint4* wf = reinterpret_cast<const uint4*>(S.g_woflag + (cg >> 1) * 96) + (lane < 20 ? lane : 0);
                uint4 f;
                it = 0;
                do { f = ld_ll16(wf); } while (!__all_sync(~0u, f.x == ep && f.y == ep && f.z == ep && f.w == ep) && ++it < SPIN_MAX);
            }
            const unsigned char* wsrc = reinterpret_cast<const unsigned char*>(S.g_wo) + (size_t)(cg * 40 + (lane & 1) * 20) * WOSTEP_B;
            const uint32_t wbar = BAR(B_WO + (lane & 1) * 4);
            mbar_wait(BAR(B_EMPTY + 2), 1);
            if (lane < 2) {
                mbar_arrive_tx(wbar, 7 * WOSTEP_B);
                bulk_g2s(sb + OFF_RING + lane * 7 * WOSTEP_B, wsrc, 7 * WOSTEP_B, wbar);
            }
            TS(3);
            mbar_wait(BAR(B_HP0), 0);
            if (lane < 2) {
                mbar_arrive_tx(wbar + 8, 7 * WOSTEP_B);
                bulk_g2s(sb + OFF_QST + lane * WOSTEP_B, wsrc + 7 * WOSTEP_B, WOSTEP_B, wbar + 8);
                bulk_g2s(sb + OFF_KV + lane * 6 * WOSTEP_B, wsrc + 8 * WOSTEP_B, 6 * WOSTEP_B, wbar + 8);
            }
            mbar_wait(BAR(B_ATT), 0);
            if (lane < 4) {
                const int q = lane >> 1;
                mbar_arrive_tx(wbar + 16 + q * 8, 3 * WOSTEP_B);
                bulk_g2s(sb + OFF_KV + KVR + ((lane & 1) * 6 + q * 3) * WOSTEP_B, wsrc + (14 + q * 3) * WOSTEP_B, 3 * WOSTEP_B, wbar + 16 + q * 8);
            }
            TS(4);
            mbar_wait(BAR(B_FFN), 0);
            TS(5);
            mbar_wait(BAR(B_STAT), 0);
            if (lane == 0 && bid < 96) {
                mbar_arrive_tx(BAR(B_GU), 40960);
                bulk_g2s(sb + OFF_GU, S.g_gu + bid * 2560, 40960, BAR(B_GU));
            }
            if (lane == 1 && bid >= 88) {
                mbar_arrive_tx(BAR(B_DN), 49152);
                bulk_g2s(sb + OFF_DN, S.g_dn + (bid - 88) * 3072, 49152, BAR(B_DN));
            }
        } else {
            if (aw == 1) {
                mbar_wait(BAR(B_X + VQ_PF), 0);
                if (lane < 20) {
                    const __nv_bfloat16* pf = P.wqkv + (size_t)bid * 5 * 1920 + (lane < 10 ? 1280 + lane * 64 : lane * 64 - 640);
#pragma unroll
                    for (int i = 0; i < 5; ++i) asm volatile("prefetch.global.L2 [%0];" ::"l"(pf + i * 1920) : "memory");
                }
                if (bid >= 28) {
                    mbar_wait(BAR(B_KREP), 0);
                    mbar_wait(BAR(B_KREP), 1);
                    const uint4* rp = dq0 + (lane >> 3) * 80 + 6400;
                    const uint32_t rbk = __reduce_or_sync(~0u, ld_flag(rp) | ld_flag(rp + 320) | ld_flag(rp + 6400) | ld_flag(rp + 6720));
                    if (lane == 0) st_flag(&S.g_wflag[160 + rp_line * 16 + rp_kc], ep | (rbk & P.zero));
                }
                TS(0);
#pragma unroll 1
                for (int kv = 0; kv < 2; ++kv) {
                    mbar_wait(BAR(B_KOWN + kv), 0);
                    if (lane >= 8 && lane < 12 && !(kv && VDIRECT)) {
                        bulk_s2g(gk + kv * 2 * KP + (lane & 1) * (kv ? VP : KP), sk + kv * KP, kv ? VP : KP);
                        asm volatile("cp.async.bulk.commit_group;\ncp.async.bulk.wait_group 0;" ::: "memory");
                    }
                    __syncwarp();
                    TS(6 + kv);
                    {
                        const unsigned char* rp = gk + (ptrdiff_t)(4 + (lane >> 4) - (lane >> 1)) * (2 * KVH) + kv * 2 * KP + (lane & 15) * 64;
                        uint32_t rbk = 0;
#pragma unroll
                        for (int i = 0; i < 12; ++i) if (i < 10 || kv) rbk |= ld_flag(rp + i * 1024);
                        rbk = __reduce_or_sync(~0u, rbk);
                        if (lane == 0) st_flag(&S.g_kvflag[(hg * 16 + rb) * 32 + kv], ep | (rbk & P.zero));
                    }
                    TS(1 + 2 * kv);
                    if (!kv) {
                        const uint4 zz = make_uint4(0, 0, 0, 0);
                        uint4* z = &S.g_o[(size_t)((((ep & 1) * 32 + rb * 2) * 4) * 40 + hg * 5) * 32 + lane];
#pragma unroll 1
                        for (int i = 0; i < 8; ++i)
#pragma unroll
                            for (int u = 0; u < 5; ++u) z[(i * 40 + u) * 32] = zz;
#pragma unroll
                        for (int i = 0; i < 4; ++i) S.g_stat[(rb64 * 64 + i * 16 + (lane >> 1)) * 8 + cg * 2 + (lane & 1)] = zz;
#pragma unroll
                        for (int i = 0; i < 8; ++i) if (lane < 20) S.g_row[(rb64 * 4 + (i >> 1)) * 160 + cg * 40 + (i & 1) * 20 + lane] = zz;
                        if (lane < 8 && bid < 96) S.g_act[bid * 8 + lane] = zz;
                        if (lane < 16 && cg == 0) S.g_cand[((lane >> 1) * 32 + rb64) * 8 + (lane & 1)] = zz;
                    }
                }
                {
                    mbar_wait(BAR(B_MFREE), 0);
                    for (int b = 0; b < first * 2; ++b)
                        for (int i = lane; i < KVH / 16; i += 32)
                            *reinterpret_cast<uint4*>(smem + OFF_KV + (b & 1) * KVR + (b >> 1) * KVH + i * 16) = make_uint4(0, 0, (i >> 6) == 7 ? 0xFF7F0000u : 0u, 0);
                    fence_async_smem();
                    __syncwarp();
                    if (lane == 0) mbar_arrive(BAR(B_VREM));
                }
                {
                    uint4* z = &S.g_o[(size_t)((((~ep & 1) * 32 + rb * 2) * 4) * 40 + hg * 5) * 32 + lane];
#pragma unroll 1
                    for (int i = 0; i < 8; ++i)
#pragma unroll
                        for (int u = 0; u < 5; ++u) z[(i * 40 + u) * 32] = make_uint4(0, 0, 0, 0);
                }
                if (lane == 0) {
                    const int b0 = bid < 96 ? 0 : 10, b1 = bid >= 88 ? 22 : 10;
                    auto pref = [&](int b) {
                        const int m = b < 5 ? 0 : b < 10 ? 1 : 2;
                        if (b < b1)
                            asm volatile("cp.async.bulk.prefetch.tensor.2d.L2.global [%0, {%1,%2}];" ::"l"(&M.w[m]), "r"((m < 2 ? bid : bid - 88) * 16), "r"((b - m * 5) * 128) : "memory");
                    };
                    auto issue = [&](int b) {
                        const int m = b < 5 ? 0 : b < 10 ? 1 : 2;
                        pref(b + 2);
                        mbar_arrive_tx(BAR(B_STG + (b & 1)), 4096);
                        tma_2d(sb + OFF_STG + (b & 1) * 4096, &M.w[m], (m < 2 ? bid : bid - 88) * 16, (b - m * 5) * 128, BAR(B_STG + (b & 1)));
                    };
                    issue(b0);
#pragma unroll 1
                    for (int b = b0; b < b1; ++b) {
                        if (b + 1 < b1) {
                            asm volatile("cp.async.bulk.wait_group.read 0;" ::: "memory");
                            issue(b + 1);
                        }
                        mbar_wait(BAR(B_STG + (b & 1)), ((b - b0) >> 1) & 1);
                        bulk_s2g(b < 10 ? S.g_gu + bid * 2560 + b * 256 : S.g_dn + (bid - 88) * 3072 + (b - 10) * 256, sb + OFF_STG + (b & 1) * 4096, 4096);
                        asm volatile("cp.async.bulk.commit_group;" ::: "memory");
                    }
                    asm volatile("cp.async.bulk.wait_group 0;" ::: "memory");
                    mbar_arrive(BAR(B_FFN));
                }
                TS(5);
            } else {
                const int a2 = aw - 2;
                mbar_wait(BAR(B_X + VQ_AFTER), 0);
                TS(0);
                if (bid < 80) {
                    mbar_wait(BAR(B_XDONE), 0);
                    uint32_t tn = clock() + MOD_T0 + a2 * (MOD_DT / 2);
                    float* sl = reinterpret_cast<float*>(smem + OFF_MT + 4096) + a2 * 320;
#pragma unroll
                    for (int i = 0; i < 10; ++i) sl[lane + 32 * i] = silu_bf(P.c[a2 * 320 + lane + 32 * i]);
                    __syncwarp();
                    sl += lane >> 2;
                    const uint4* s = reinterpret_cast<const uint4*>(smem + OFF_KV + a2 * KVR + KP) + lane;
                    float acc[8];
#pragma unroll
                    for (int i = 0; i < 8; ++i) acc[i] = 0.f;
                    const __nv_bfloat16* gs = P.wmod + (size_t)(a2 * 320 + (lane >> 2)) * 3840 + 1280 + bid * 32 + (lane & 3) * 8;
                    uint32_t ds = sb + OFF_KV + a2 * KVR + KP + lane * 16;
#pragma unroll 1
                    for (int bt = 0; bt < 5; ++bt) {
                        if (bt < 4) {
                            while ((int)(clock() - tn) < 0) __nanosleep(40);
                            tn += MOD_DT;
#pragma unroll
                            for (int i = 0; i < 10; ++i)
                                asm volatile("cp.async.cg.shared.global.L2::128B [%0], [%1], 16;" ::"r"(ds + i * 512), "l"(gs + (size_t)i * 8 * 3840) : "memory");
                            gs += (size_t)80 * 3840; ds += KVH;
                        }
                        asm volatile("cp.async.commit_group;" ::: "memory");
                        if (bt) {
                            asm volatile("cp.async.wait_group 1;" ::: "memory");
#pragma unroll
                            for (int j = 0; j < 2; ++j) {
#pragma unroll
                                for (int i = 0; i < 5; ++i) fma8(acc, sl[(j * 5 + i) * 8], s[(j * 5 + i) * 32]);
                                asm volatile("" ::: "memory");
                            }
                            s += KVH / 16; sl += 80;
                        }
                    }
                    fence_async_smem();
                    __syncwarp();
                    if (lane == 0) mbar_arrive(BAR(B_MFREE));
                    float r = treduce8(acc, lane);
                    float* red2 = reinterpret_cast<float*>(smem + OFF_RED2);
                    if (a2 == 1) red2[lane] = r;
                    bar_sync(7, 64);
                    if (a2 == 0) {
                        r = rbf(r + red2[lane]);
                        const int pr = (lane & 3) * 4 + ((lane >> 2) & 1) * 2 + ((lane >> 3) & 1);
                        const float hi = __shfl_xor_sync(~0u, r, 16);
                        if (lane < 16) st_ll8(&S.g_mod[bid * 16 + pr], pack_bf16(r, hi), ep);
                        if (bid >= 20 && bid < 60) {
                            float q = (bid < 40 ? r : rbf(1.0f + r)) * __bfloat162float(P.wr[(bid % 20) * 32 + pr * 2 + (lane >> 4)]);
#pragma unroll
                            for (int o = 16; o > 0; o >>= 1) q += __shfl_xor_sync(~0u, q, o);
                            if (lane == 0) st_ll8(&S.g_msum[bid - 20], __float_as_uint(q), ep);
                        }
                    }
                }
                else if (lane == 0) mbar_arrive(BAR(B_MFREE));
                TS(3);
                if (bid >= 48) {
                    const int k8 = bid - 48, hs = k8 / 10, pos = (int)((0x7695432810ull >> (4 * (k8 - hs * 10))) & 15);
                    const __nv_bfloat16* s = P.wo + (size_t)(k8 * 8 + (lane >> 2)) * DM + a2 * 320 + (lane & 3) * 8;
                    const int step = (hs >> 2) * 20 + (pos < 6 ? (hs & 3) * 3 : 9 + (hs & 3) * 2) + (pos >> 1);
                    uint32_t* d = reinterpret_cast<uint32_t*>(S.g_wo) + (size_t)a2 * 2 * 51200 + (step * 2 + (pos & 1)) * 640 + lane;
#pragma unroll 1
                    for (int q = 0; q < 2; ++q) {
                        uint4 v[5];
#pragma unroll
                        for (int i = 0; i < 5; ++i) v[i] = ldg_nc(s + q * 160 + i * 32);
#pragma unroll
                        for (int i = 0; i < 5; ++i) {
                            uint32_t* dd = d + q * 51200 + i * 128;
                            dd[0] = v[i].x; dd[32] = v[i].y; dd[64] = v[i].z; dd[96] = v[i].w;
                        }
                    }
                    uint32_t rbk = 0;
#pragma unroll
                    for (int i = 0; i < 40; ++i) rbk |= ld_flag(d + (i / 20) * 51200 + (i % 20) * 32);
                    rbk = __reduce_or_sync(~0u, rbk);
                    if (lane == 0) st_flag(&S.g_woflag[a2 * 96 + k8], ep | (rbk & P.zero));
                }
                TS(2);
                {
                    const int i = at - 64;
                    const uint2* p0 = i < 40 ? &S.g_mod[cg * 80 + 2 * i] : i < 60 ? &S.g_msum[2 * (i - 40)] : &S.g_mod[960 + max(bid - 88, 0) * 8 + 2 * (i - 60)];
                    const int st = i < 40 ? 320 : 0;
                    const uint2 wr = reinterpret_cast<const uint2*>(P.wr)[cg * 40 + min(i, 39)];
                    uint4 va, vs, vc, vg;
                    uint32_t it = 0;
                    do {
                        va = ld_ll16(p0); vs = ld_ll16(p0 + st); vc = ld_ll16(p0 + 2 * st); vg = ld_ll16(p0 + 3 * st);
                    } while (!(va.y == ep && va.w == ep && vs.y == ep && vs.w == ep && vc.y == ep && vc.w == ep && vg.y == ep && vg.w == ep) && ++it < SPIN_MAX);
                    __syncwarp();
                    if (i < 40) {
                        const uint32_t c0 = pack_bf16(1.0f + bf_lo(vc.x), 1.0f + bf_hi(vc.x)), c1 = pack_bf16(1.0f + bf_lo(vc.z), 1.0f + bf_hi(vc.z));
                        uint2* tb = reinterpret_cast<uint2*>(smem + OFF_TAB) + i;
                        tb[0] = make_uint2(va.x, va.z); tb[40] = make_uint2(c0, c1); tb[80] = make_uint2(vs.x, vs.z); tb[120] = make_uint2(vg.x, vg.z);
                        uint32_t* tw = reinterpret_cast<uint32_t*>(smem + OFF_TABW) + (i >> 3) * 64 + (i & 7);
#pragma unroll
                        for (int e = 0; e < 2; ++e) {
                            const uint32_t cc = e ? c1 : c0, ww = e ? wr.y : wr.x;
                            const float g0 = bf_lo(cc) * bf_lo(ww), g1 = bf_hi(cc) * bf_hi(ww);
                            const uint32_t hi = pack_bf16(g0, g1);
                            tw[e * 8] = 0x3F803F80u; tw[e * 8 + 16] = hi; tw[e * 8 + 32] = pack_bf16(g0 - bf_lo(hi), g1 - bf_hi(hi)); tw[e * 8 + 48] = 0u;
                        }
                    } else if (i >= 60) {
                        reinterpret_cast<float4*>(smem + OFF_GBD)[i - 60] = make_float4(bf_lo(va.x), bf_hi(va.x), bf_lo(va.z), bf_hi(va.z));
                    }
                    if (a2 == 1) {
                        const float q = __uint_as_float(va.x) + __uint_as_float(va.z);
                        float sbw = (i >= 40 && i < 50) ? q : 0.f, sg = (i >= 50 && i < 60) ? q : 0.f;
#pragma unroll
                        for (int o = 16; o > 0; o >>= 1) { sg += __shfl_xor_sync(~0u, sg, o); sbw += __shfl_xor_sync(~0u, sbw, o); }
                        if (lane == 0) *reinterpret_cast<float2*>(smem + OFF_CONST) = make_float2(sg, sbw);
                    }
                    mbar_arrive(BAR(B_MOD2));
                    TS(4);
                }
                if (a2 == 1) {
                    mbar_wait(BAR(B_STAT), 0);
                    uint4 cnd;
                    uint32_t it = 0;
                    do { cnd = ld_ll16(&S.g_cand[((bid & 7) * 32 + lane) * 8]); } while (!(cnd.y == ep && cnd.w == ep) && ++it < SPIN_MAX);
                    const uint32_t k1 = __reduce_max_sync(~0u, cnd.x);
                    const uint32_t k2 = __reduce_max_sync(~0u, cnd.x == k1 ? cnd.z : cnd.x);
                    if (lane == 0) {
                        *reinterpret_cast<uint2*>(smem + OFF_CAND + 64) = make_uint2(k1, k2);
                        mbar_arrive(BAR(B_TOP));
                    }
                    TS(5);
                }
            }
        }
    } else {
        const int wg = warp >> 2, w = warp & 3, g = lane >> 2, t = lane & 3;
        uint4* dq = dq0 + warp * 80 + (lane >> 3);
        {
            ep = ld_flag(&S.g_epoch);
            float sl[5];
            if (mj >= 0) {
#pragma unroll
                for (int i = 0; i < 5; ++i) sl[i] = silu_bf(cv[i]);
            }
            bar_sync(0, NTHR);
            TS(20);
            uint4* d = dq;
            ep += 1;
            if (mj >= 0) {
                float acc[8];
#pragma unroll
                for (int i = 0; i < 8; ++i) acc[i] = 0.f;
#pragma unroll
                for (int i = 0; i < 5; ++i) fma8(acc, sl[i], mv[i]);
                float* red = reinterpret_cast<float*>(smem + OFF_RED);
                red[warp * 32 + lane] = treduce8(acc, lane);
                TS(22);
            }
            if (mj >= 0) {
                const float* red = reinterpret_cast<const float*>(smem + OFF_RED);
                bar_sync(6, 256);
                if (warp == 0) {
                    float r = 0.f;
#pragma unroll
                    for (int i = 0; i < 8; ++i) r += red[i * 32 + lane];
                    const uint32_t lo = ((__float_as_uint(r) + 0x80u) & ~0xFFu) | ((lane < 16 ? ep : ep >> 8) & 0xFFu);
                    const uint32_t hi = __shfl_xor_sync(~0u, lo, 16);
                    if (lane < 16)
                        st_ll8(reinterpret_cast<uint2*>(S.g_mod1) + (mj & 1) * 640 + (mj >> 1) * 16 + t * 4 + ((lane >> 2) & 1) * 2 + (lane >> 3), lo, hi);
                }
            }
            if (bid >= 28) {
                d[0] = kr[0]; d[4] = kr[1];
                __syncwarp();
                if (lane == 0) mbar_arrive(BAR(B_KREP));
                TS(21);
            }
            asm volatile("setmaxnreg.inc.sync.aligned.u32 232;");
            TS(19);
        }
        uint32_t qf[20];
        {
            uint32_t a[160];
            uint4 vq[4];
            const uint4* mp = &S.g_mod1[tid];
            const int mo = 256 - (warp >> 1) * 64;
            uint32_t lr[2], ln[2];
            {
                float cs_[2][4], qa[2][4], qb[2][4];
#pragma unroll
                for (int i = 0; i < 8; ++i) cs_[i >> 2][i & 3] = qa[i >> 2][i & 3] = qb[i >> 2][i & 3] = 0.f;
                const uint32_t xa = sb + OFF_X + (warp * 16 + (lane & 15)) * 128;
                uint32_t xo[4];
#pragma unroll
                for (int s = 0; s < 4; ++s) xo[s] = xa + (((2 * s + (lane >> 4)) ^ (lane & 7)) << 4);
#pragma unroll
                for (int kc = 0; kc < 10; ++kc) {
                    if (kc == MOD_AT) {
#pragma unroll
                        for (int i = 0; i < 4; ++i) mv[i] = ld_ll16(mp + (i & 1) * 320 + (i >> 1) * mo);
                    }
                    if (kc == VQ_AT && bid >= 28) {
                        const __nv_bfloat16* s = P.wqkv + (size_t)(rp_kc * 64 + warp * 8 + (lane >> 3)) * 1920 + rp_line * 64 + (lane & 7) * 8;
                        vq[0] = ldg_nc(s + 1280); vq[1] = ldg_nc(s + 1280 + 4 * 1920); vq[2] = ldg_nc(s); vq[3] = ldg_nc(s + 4 * 1920);
                    }
                    mbar_wait(BAR(B_X + kc), 0);
                    if (kc == 0) TS(23);
                    if (kc == 4) TS(24);
                    if (kc == 9) TS(25);
#pragma unroll
                    for (int s = 0; s < 4; ++s) {
                        const int o = (kc * 4 + s) * 4;
                        ldmatrix4(a[o], a[o + 1], a[o + 2], a[o + 3], xo[s] + kc * 16384);
                    }
#pragma unroll
                    for (int s = 0; s < 4; ++s) {
                        const int o = (kc * 4 + s) * 4;
                        const uint32_t wq[4] = {a[o], a[o + 1], a[o + 2], a[o + 3]};
                        mma16816(cs_[s & 1], wq, 0x3F803F80u, 0x3F803F80u);
                        mma16816(qa[s & 1], wq, wq[0], wq[2]);
                        mma16816(qb[s & 1], wq, wq[1], wq[3]);
                    }
                }
                if (lane == 0) mbar_arrive(BAR(B_XDONE));
#pragma unroll
                for (int r = 0; r < 2; ++r) {
                    float dg = 0.f;
#pragma unroll
                    for (int i = 0; i < 2; ++i) dg += r == 0 ? ((g & 1) ? qa[i][1] : qa[i][0]) : ((g & 1) ? qb[i][3] : qb[i][2]);
                    const float v = __shfl_sync(~0u, dg, (lane & ~3) + (g >> 1));
                    const float mean = (cs_[0][2 * r] + cs_[1][2 * r]) * (1.0f / DM);
                    const float var = fmaxf(v * (1.0f / DM) - mean * mean, 0.f);
                    const float rs = rsqrtf(var + 1e-5f);
                    lr[r] = pack_bf16(rs, rs);
                    ln[r] = pack_bf16(-mean * bf_lo(lr[r]), -mean * bf_lo(lr[r]));
                }
            }
            TS(0);
            {
                if (bid >= 28) {
                    const int cc = rp_line * 8 + ((lane | P.zero) & 7), hh = cc / 10;
                    uint4* dq = S.g_wq + (size_t)(hh * 240 + rp_kc * 8 + warp) * 80 + (cc - hh * 10) * 8 + (lane >> 3);
#pragma unroll
                    for (int i = 0; i < 4; ++i) dq[(1 + (i >> 1)) * 6400 + (i & 1) * 4] = vq[i];
                    __syncwarp();
                    if (lane == 0) mbar_arrive(BAR(B_KREP));
                }
                do {
#pragma unroll
                    for (int i = 0; i < 160; ++i) hfma2_ip(a[i], lr[i & 1], ln[i & 1]);
                } while (P.zero);
                const uint32_t e = ep;
                uint32_t it = 0;
                for (;;) {
                    bool ok = true;
#pragma unroll
                    for (int i = 0; i < 4; ++i)
                        ok = ok && __byte_perm(mv[i].x, mv[i].y, 0x4440) == __byte_perm(e, 0, 0x1110) && __byte_perm(mv[i].z, mv[i].w, 0x4440) == __byte_perm(e, 0, 0x1110);
                    if (ok || ++it >= SPIN_MAX) break;
#pragma unroll
                    for (int i = 0; i < 4; ++i) mv[i] = ld_ll16(mp + (i & 1) * 320 + (i >> 1) * mo);
                }
                uint32_t* mt = reinterpret_cast<uint32_t*>(smem + OFF_MT) + (lane >> 2) * 16 + (lane & 1) * 8 + ((lane >> 1) & 1);
#pragma unroll
                for (int i = 0; i < 2; ++i) {
                    const int wq = i ? 8 + (warp & 1) : warp;
                    const uint4 &u = mv[2 * i], &v = mv[2 * i + 1];
                    uint32_t m0 = pack_bf16(__uint_as_float(u.x & ~0xFFu) + __uint_as_float(v.x & ~0xFFu), __uint_as_float(u.y & ~0xFFu) + __uint_as_float(v.y & ~0xFFu));
                    uint32_t m1 = pack_bf16(__uint_as_float(u.z & ~0xFFu) + __uint_as_float(v.z & ~0xFFu), __uint_as_float(u.w & ~0xFFu) + __uint_as_float(v.w & ~0xFFu));
                    if (wq >= 5) { m0 = hadd2_bf16(m0, 0x3F803F80u); m1 = hadd2_bf16(m1, 0x3F803F80u); }
                    uint32_t* d = mt + (wq >= 5 ? (wq - 5) * 128 : wq * 128 + 2);
                    d[0] = m0; d[4] = m1;
                }
                bar_sync(6, 256);
            }
            TS(1);
            float acc[40];
            uint32_t vt[24];
            uint4 mt[4];
            uint32_t mta = sb + OFF_MT + t * 16;
            auto ld_mt = [&]() { lds128<0>(mt[0], mta); lds128<64>(mt[1], mta); lds128<128>(mt[2], mta); lds128<192>(mt[3], mta); };
            [[maybe_unused]] uint32_t twait = 1;
            const uint64_t dring = mkdesc(sb + OFF_RING, 1280, 128);
            const uint32_t stb = sb + OFF_KV + (4 + wg) * KVH + (w * 16 + (lane & 15)) * 16;
            const uint32_t st0 = stb + (lane >> 4) * 1024, st2 = stb + ((lane >> 4) ? KVR : 4096);
#pragma unroll
            for (int p = 0; p < 3; ++p) {
#pragma unroll
                for (int kc = 0; kc < 10; ++kc) {
                    const int c = p * 5 + (kc >> 1), slot = c & 3;
                    if (p == 0) {
                        if (kc == 0) ld_mt();
#pragma unroll
                        for (int i = 0; i < 16; ++i) hfma2_ip(a[kc * 16 + i], (i & 2) ? mt[i >> 2].y : mt[i >> 2].x, (i & 2) ? mt[i >> 2].w : mt[i >> 2].z);
                        if (kc < 9) { mta += 256 + (a[kc * 16 + 15] & P.zero); ld_mt(); }
                    }
                    if (!(kc & 1)) TW(twait, mbar_wait(BAR(B_FULL + slot), (c >> 2) & 1));
                    if (p == 0 || !(kc & 1)) WG_FENCE();
#pragma unroll
                    for (int s = 0; s < 4; ++s) {
                        const int o = (kc * 4 + s) * 4;
                        const uint64_t db = dring + (uint64_t)((slot * CHUNK_B + ((kc & 1) * 4 + s) * 2560) >> 4);
                        if (kc == 0 && s == 0) wgmma_n80_init(acc, a[o], a[o + 1], a[o + 2], a[o + 3], db);
                        else wgmma_n80(acc, a[o], a[o + 1], a[o + 2], a[o + 3], db);
                    }
                    WG_COMMIT();
                    if (VDIRECT && p == 2 && kc == 1) {
                        uint32_t* gv = reinterpret_cast<uint32_t*>(S.g_kv) + (size_t)(hg * 32 + rb * 2 + wg) * (2 * KVH / 4) + 2 * KP / 4 + w * 64 + lane;
#pragma unroll
                        for (int i = 0; i < 24; ++i) gv[(i >> 1) * 256 + (i & 1) * 32] = vt[i];
                        __syncwarp();
                        if (lane == 0) mbar_arrive(BAR(B_VOWN));
                    }
                    if (kc > 0 && !(kc & 1)) {
                        WG_WAIT(1);
                        if (lane == 0) mbar_arrive(BAR(B_EMPTY + ((c - 1) & 3)));
                    }
                }
                WG_WAIT(0);
                pin(acc);
                if (lane == 0) mbar_arrive(BAR(B_EMPTY + ((p * 5 + 4) & 3)));
                TS(2 + p);
                TSV(26 + p, twait);
                if (p == 0) {
#pragma unroll
                    for (int jj = 0; jj < 5; ++jj)
                        stmatrix4(jj < 2 ? st0 + jj * 2048 : (jj == 2 ? st2 : st0 + KVR + (2 * jj - 5) * 1024),
                                  pack_bf16(acc[8 * jj + 0], acc[8 * jj + 1]), pack_bf16(acc[8 * jj + 2], acc[8 * jj + 3]),
                                  pack_bf16(acc[8 * jj + 4], acc[8 * jj + 5]), pack_bf16(acc[8 * jj + 6], acc[8 * jj + 7]));
                    fence_async_smem();
                    __syncwarp();
                    if (lane == 0) mbar_arrive(BAR(B_KOWN));
                } else if (p == 1) {
#pragma unroll
                    for (int hp = 0; hp < 2; ++hp) {
#pragma unroll
                        for (int r = 0; r < 2; ++r) {
                            auto pk = [&](int j) { return pack_bf16(acc[4 * j + 2 * r], acc[4 * j + 2 * r + 1]); };
                            const uint32_t mid = pk(5 * hp + 2);
                            vt[(6 * hp + 0) * 2 + r] = pk(5 * hp + 0);
                            vt[(6 * hp + 1) * 2 + r] = pk(5 * hp + 1);
                            vt[(6 * hp + 2) * 2 + r] = t < 2 ? mid : (t == 2 ? 0x00003F80u : 0u);
                            vt[(6 * hp + 3) * 2 + r] = pk(5 * hp + 3);
                            vt[(6 * hp + 4) * 2 + r] = pk(5 * hp + 4);
                            vt[(6 * hp + 5) * 2 + r] = t >= 2 ? mid : (t == 0 ? 0x00003F80u : 0u);
                        }
                    }
#pragma unroll
                    for (int jj = 0; jj < 6; ++jj)
                        stmatrix4(st0 + (jj / 3) * KVR + KP + (jj % 3) * 2048, vt[4 * jj], vt[4 * jj + 1], vt[4 * jj + 2], vt[4 * jj + 3]);
                    fence_async_smem();
                    if (!VDIRECT) {
                        __syncwarp();
                        if (lane == 0) mbar_arrive(BAR(B_VOWN));
                    }
                } else {
#pragma unroll
                    for (int i = 0; i < 20; ++i) qf[i] = pack_bf16(acc[2 * i], acc[2 * i + 1]);
                }
            }
        }
        {
            uint32_t qh[24];
#pragma unroll
            for (int h = 0; h < 4; ++h) {
                const int jb = (h >> 1) * 5 + (h & 1) * 3, xb = (h >> 1) * 5 + 2;
                const bool keep = (h & 1) ? (t >= 2) : (t < 2);
#pragma unroll
                for (int i = 0; i < 4; ++i) qh[h * 6 + i] = qf[2 * jb + i];
                qh[h * 6 + 4] = keep ? qf[2 * xb] : 0u;
                qh[h * 6 + 5] = keep ? qf[2 * xb + 1] : 0u;
            }
            const int bmin = 4 - min(4, rb * 2 + wg);
            const int thr = w * 16 + g - 2 * t;
            uint32_t msk[9];
#pragma unroll
            for (int k = 0; k < 9; ++k) msk[k] = ((8 * (k - 1) > thr) ? 0xFFFFu : 0u) | ((8 * (k - 1) + 1 > thr) ? 0xFFFF0000u : 0u);
            const float cs = 0.22360679774997896f * 1.4426950408889634f;
            uint4* go = &S.g_o[(size_t)((((ep & 1) * 32 + rb * 2 + wg) * 4 + w) * 40 + hg * 5) * 32 + lane];
            const bool sw = hg >= 4;
            uint32_t oa0 = 0, oa1 = 0, oc0 = 0, oc1 = 0;
            mbar_wait(BAR(B_VOWN), 0);
            mbar_wait(BAR(B_KREM), 0);
            TS(5);
            if (wg == 1) bar_arrive(4, 256);
#pragma unroll 1
            for (int h = 0; h < 4; ++h) {
                const uint32_t kvb = sb + OFF_KV + wg * KVH + (h >> 1) * KVR;
                const uint64_t dke = mkdesc(kvb + 2048, 1024, 128);
                const uint64_t dk = mkdesc(kvb + (h & 1) * 3072, 1024, 128), dv = mkdesc(kvb + KP + (h & 1) * 3072, 128, 1024);
                float sc[5][32];
                if (h == 2) mbar_wait(BAR(B_REM1), 0);
                WG_FENCE();
#pragma unroll
                for (int b = 0; b < 5; ++b) {
                    wgmma_n64_init(sc[b], qh[0], qh[1], qh[2], qh[3], dk + (uint64_t)((b * KVH) >> 4));
                    wgmma_n64(sc[b], qh[4], qh[5], 0u, 0u, dke + (uint64_t)((b * KVH) >> 4));
                }
                WG_COMMIT();
                WG_WAIT(0);
#pragma unroll
                for (int b = 0; b < 5; ++b) pin(sc[b]);
#pragma unroll
                for (int i = 0; i < 18; ++i) qh[i] = qh[i + 6];
                if (__builtin_expect(bmin > 0, 0)) {
#pragma unroll
                    for (int b = 0; b < 4; ++b)
                        if (b < bmin) {
#pragma unroll
                            for (int i = 0; i < 32; ++i) asm volatile("mov.b32 %0, 0xFF800000;" : "=f"(sc[b][i]));
                        }
                }
#pragma unroll
                for (int i = 0; i < 32; ++i) {
                    const int cc = 8 * (i >> 2) + (i & 1) - 8 * ((i >> 1) & 1);
                    sc[0][i] = cc > thr ? sc[0][i] : sc[4][i];
                }
                float mx[2][4];
#pragma unroll
                for (int b = 0; b < 4; ++b) {
                    mx[0][b] = fmaxf(sc[b][0], sc[b][1]); mx[1][b] = fmaxf(sc[b][2], sc[b][3]);
#pragma unroll
                    for (int i = 4; i < 32; ++i) mx[(i >> 1) & 1][b] = fmaxf(mx[(i >> 1) & 1][b], sc[b][i]);
                }
                float mc[2];
#pragma unroll
                for (int r = 0; r < 2; ++r) {
                    float m = fmaxf(fmaxf(mx[r][0], mx[r][1]), fmaxf(mx[r][2], mx[r][3]));
                    m = fmaxf(m, __shfl_xor_sync(~0u, m, 1));
                    m = fmaxf(m, __shfl_xor_sync(~0u, m, 2));
                    mc[r] = -m * cs;
                }
                mbar_wait(BAR(B_VREM), 0);
                float o[12];
                bar_sync(4 + wg, 256);
#pragma unroll
                for (int b = 0; b < 4; ++b) {
                    uint32_t pp[16];
#pragma unroll
                    for (int i = 0; i < 16; ++i)
                        pp[i] = pack_bf16(ex2(fmaf(sc[b][2 * i], cs, mc[i & 1])), ex2(fmaf(sc[b][2 * i + 1], cs, mc[i & 1])));
                    if (b == PP_B && wg + h < 4) bar_arrive(5 - wg, 256);
                    if (b == 0) {
                        uint32_t pn[16];
#pragma unroll
                        for (int i = 0; i < 16; ++i) {
                            const uint32_t m = msk[(i >> 1) - (i & 1) + 1];
                            pn[i] = pp[i] & ~m; pp[i] &= m;
                        }
                        WG_FENCE();
#pragma unroll
                        for (int kk = 0; kk < 4; ++kk) {
                            const uint64_t d = dv + (uint64_t)((4 * KVH + kk * 256) >> 4);
                            if (kk == 0) wgmma_n24_init(o, pn[0], pn[1], pn[2], pn[3], d);
                            else wgmma_n24(o, pn[4 * kk], pn[4 * kk + 1], pn[4 * kk + 2], pn[4 * kk + 3], d);
                        }
                    } else {
                        WG_FENCE();
                    }
#pragma unroll
                    for (int kk = 0; kk < 4; ++kk)
                        wgmma_n24(o, pp[4 * kk], pp[4 * kk + 1], pp[4 * kk + 2], pp[4 * kk + 3], dv + (uint64_t)((b * KVH + kk * 256) >> 4));
                    WG_COMMIT();
                }
                WG_WAIT(0);
                pin(o);
                if ((h & 1) && lane == 0) mbar_arrive(BAR(B_HP0) + (h >> 1) * 8);
                const int src = (lane & ~3) + ((h & 1) ? 0 : 2);
                const float i0 = rcp(__shfl_sync(~0u, o[8], src)), i1 = rcp(__shfl_sync(~0u, o[10], src));
                uint32_t po[6];
#pragma unroll
                for (int i = 0; i < 3; ++i) {
                    const uint32_t r0 = pack_bf16(o[4 * i] * i0, o[4 * i + 1] * i0), r1 = pack_bf16(o[4 * i + 2] * i1, o[4 * i + 3] * i1);
                    po[2 * i] = sw ? r1 : r0; po[2 * i + 1] = sw ? r0 : r1;
                }
                st_b128(go + h * 32, po[0] ? po[0] : 0x8000u, po[1], po[2], po[3]);
                if (h == 2) { oa0 = oc0; oa1 = oc1; }
                if (!(h & 1) || t >= 2) { oc0 = po[4]; oc1 = po[5]; }
                TS(6 + h);
            }
            st_b128(go + 4 * 32, oa0 ? oa0 : 0x8000u, oa1, oc0 ? oc0 : 0x8000u, oc1);
        }
        const int row = rb64 * 64 + w * 16 + g + 8 * wg;
        const uint4* sp = &S.g_stat[row * 8 + t * 2];
        uint4 pa, pb;
        uint32_t x1[20];
        {
            uint4 af[20];
            const uint4* gi = &S.g_o[(size_t)((((ep & 1) * 32 + rb64) * 4 + w) * 40 + wg * 20) * 32 + lane];
#pragma unroll
            for (int u = 0; u < 12; ++u) af[u] = ld_b128(gi + ((u / 3) * 5 + u % 3) * 32);
#pragma unroll
            for (int i = 0; i < 8; ++i) af[12 + i] = ld_b128(gi + ((i >> 1) * 5 + 3 + (i & 1)) * 32);
            const __nv_bfloat16* xp = P.x + (size_t)row * DM + cg * 160 + t * 8;
#pragma unroll
            for (int i = 0; i < 5; ++i) {
                const uint4 q = ldg_nc(xp + i * 32);
                x1[4 * i] = q.x; x1[4 * i + 1] = q.y; x1[4 * i + 2] = q.z; x1[4 * i + 3] = q.w;
            }
            float acc[80];
            const uint64_t d0 = mkdesc(sb + OFF_RING + wg * 7 * WOSTEP_B, 2560, 128), d7 = mkdesc(sb + OFF_QST + wg * WOSTEP_B, 2560, 128), d1 = mkdesc(sb + OFF_KV + wg * 6 * WOSTEP_B, 2560, 128);
#pragma unroll
            for (int u = 0; u < 20; ++u) {
                if (u == 0 || u == 7 || u == 14 || u == 17) mbar_wait(BAR(B_WO + wg * 4 + (u == 0 ? 0 : u == 7 ? 1 : u == 14 ? 2 : 3)), 0);
                if (u == 0) {
                    uint32_t it = 0;
                    for (;;) {
                        bool ok = true;
#pragma unroll
                        for (int i = 0; i < 12; ++i) ok = ok && af[i].x;
                        if (__all_sync(~0u, ok) || ++it >= SPIN_MAX) break;
#pragma unroll
                        for (int i = 0; i < 12; ++i) af[i] = ld_b128(gi + ((i / 3) * 5 + i % 3) * 32);
                    }
                    TS(10);
                }
                if (u == 12) {
                    WG_COMMIT();
                    uint32_t it = 0;
                    for (;;) {
                        bool ok = true;
#pragma unroll
                        for (int i = 0; i < 8; ++i) ok = ok && af[12 + i].x && (!(i & 1) || af[12 + i].z);
                        if (__all_sync(~0u, ok) || ++it >= SPIN_MAX) break;
                        if (hg >= 4) mbar_wait(BAR(B_ATT), 0);
#pragma unroll
                        for (int i = 0; i < 8; ++i) af[12 + i] = ld_b128(gi + ((i >> 1) * 5 + 3 + (i & 1)) * 32);
                    }
                    TS(29);
                }
                if (u == 0 || u == 7 || u == 12 || u == 14 || u == 17) WG_FENCE();
                const uint64_t d = u < 7 ? d0 + (uint64_t)((u * WOSTEP_B) >> 4) : u == 7 ? d7
                                         : d1 + (uint64_t)((u < 14 ? (u - 8) * WOSTEP_B : KVR + (u - 14) * WOSTEP_B) >> 4);
                if (u == 0) wgmma_n160_init(acc, af[u].x, af[u].y, af[u].z, af[u].w, d);
                else wgmma_n160(acc, af[u].x, af[u].y, af[u].z, af[u].w, d);
            }
            WG_COMMIT();
            WG_WAIT(0);
            pin(acc);
            TS(11);
            bar_sync(2 + wg, 128);
            float2* snd = reinterpret_cast<float2*>(smem + OFF_RING + wg * 7 * WOSTEP_B) + (tid & 127);
            const float2* rcv = reinterpret_cast<const float2*>(smem + OFF_RING + (1 - wg) * 7 * WOSTEP_B) + (tid & 127);
#pragma unroll
            for (int j = 0; j < 20; ++j) snd[j * 128] = make_float2(acc[4 * j + 2], acc[4 * j + 3]);
            mbar_wait(BAR(B_MOD2), 0);
            bar_sync(6, 256);
            pa = ld_ll16(sp); pb = ld_ll16(sp + 1);
#pragma unroll
            for (int i = 0; i < 5; ++i) {
                const uint4 ga = *reinterpret_cast<const uint4*>(smem + OFF_TAB + i * 64 + t * 16);
                const uint32_t gav[4] = {ga.x, ga.y, ga.z, ga.w};
#pragma unroll
                for (int jj = 0; jj < 4; ++jj) {
                    const int j = 4 * i + jj;
                    const float2 q = rcv[j * 128];
                    x1[j] = hadd2_bf16(x1[j], hmul2_bf16(gav[jj], pack_bf16(acc[4 * j] + q.x, acc[4 * j + 1] + q.y)));
                }
            }
        }
        LnCoef lc;
        uint32_t key;
        {
            float z[4] = {0.f, 0.f, 0.f, 0.f}, qa[4] = {0.f, 0.f, 0.f, 0.f}, qb[4] = {0.f, 0.f, 0.f, 0.f};
#pragma unroll
            for (int i = 0; i < 5; ++i) {
                const uint2 bw = *reinterpret_cast<const uint2*>(smem + OFF_TABW + i * 256 + lane * 8);
                const uint32_t wq[4] = {x1[4 * i], x1[4 * i + 1], x1[4 * i + 2], x1[4 * i + 3]};
                mma16816(z, wq, bw.x, bw.y);
                mma1688(qa, wq[0], wq[1], wq[0]); mma1688(qb, wq[0], wq[1], wq[1]);
                mma1688(qa, wq[2], wq[3], wq[2]); mma1688(qb, wq[2], wq[3], wq[3]);
            }
            const float s2 = __shfl_sync(~0u, (g & 1) ? qa[1] + qb[3] : qa[0] + qb[2], (lane & ~3) + (g >> 1));
            const uint32_t own = __float_as_uint(t == 3 ? s2 : z[0] + z[3]);
            st_ll8(reinterpret_cast<uint2*>(&S.g_stat[row * 8 + cg * 2]) + t, own, ep);
            TS(12);
            uint32_t it = 0;
            while (t != cg && !(pa.y == ep && pa.w == ep && pb.y == ep && pb.w == ep) && ++it < SPIN_MAX) { pa = ld_ll16(sp); pb = ld_ll16(sp + 1); }
            {
                const uint32_t v0 = __shfl_sync(~0u, own, lane & ~3), v1 = __shfl_sync(~0u, own, (lane & ~3) + 1);
                const uint32_t v2 = __shfl_sync(~0u, own, (lane & ~3) + 2), v3 = __shfl_sync(~0u, own, lane | 3);
                if (t == cg) { pa.x = v0; pa.z = v1; pb.x = v2; pb.z = v3; }
            }
            float s1 = __uint_as_float(pa.x), s3 = __uint_as_float(pa.z) + __uint_as_float(pb.x), sq = __uint_as_float(pb.z);
#pragma unroll
            for (int o = 1; o < 4; o <<= 1) { s1 += __shfl_xor_sync(~0u, s1, o); s3 += __shfl_xor_sync(~0u, s3, o); sq += __shfl_xor_sync(~0u, sq, o); }
            const float mean = s1 * (1.0f / DM);
            const float rstd = rsqrtf(fmaxf(sq * (1.0f / DM) - mean * mean, 0.f) + 1e-5f);
            lc = ln_coef(mean, rstd);
            const float2 cc = *reinterpret_cast<const float2*>(smem + OFF_CONST);
            const uint32_t rb_ = __float_as_uint(rstd * (s3 - mean * cc.x) + cc.y);
            key = (((rb_ & 0x80000000u) ? ~rb_ : (rb_ | 0x80000000u)) & 0xFFFFF800u) | (uint32_t)(2047 - row);
        }
        if (lane == 0) mbar_arrive(BAR(B_STAT));
        TS(13);
        uint32_t lk1, lk2;
        {
            const uint32_t k1 = __reduce_max_sync(~0u, key);
            const uint32_t k2 = __reduce_max_sync(~0u, key == k1 ? 0u : key);
            uint32_t* cand = reinterpret_cast<uint32_t*>(smem + OFF_CAND);
            if (lane == 0) *reinterpret_cast<uint2*>(cand + 2 * warp) = make_uint2(k1, k2);
            bar_sync(6, 256);
            const uint32_t kk = cand[lane & 15];
            lk1 = __reduce_max_sync(~0u, kk);
            lk2 = __reduce_max_sync(~0u, kk == lk1 ? 0u : kk);
            if (tid < 8) st_ll16(&S.g_cand[(tid * 32 + rb64) * 8], lk1, lk2, ep);
        }
        uint4* outp = reinterpret_cast<uint4*>(P.out + (size_t)row * DM + cg * 160) + t;
        const bool lcand = key == lk1 || key == lk2;
        uint32_t ov[20];
        {
            uint32_t h2[20];
#pragma unroll
            for (int i = 0; i < 5; ++i) {
                const uint4 c1 = *reinterpret_cast<const uint4*>(smem + OFF_TAB + 320 + i * 64 + t * 16);
                const uint4 sh = *reinterpret_cast<const uint4*>(smem + OFF_TAB + 640 + i * 64 + t * 16);
                h2[4 * i] = hfma2_bf16(ln_apply(x1[4 * i], lc), c1.x, sh.x);
                h2[4 * i + 1] = hfma2_bf16(ln_apply(x1[4 * i + 1], lc), c1.y, sh.y);
                h2[4 * i + 2] = hfma2_bf16(ln_apply(x1[4 * i + 2], lc), c1.z, sh.z);
                h2[4 * i + 3] = hfma2_bf16(ln_apply(x1[4 * i + 3], lc), c1.w, sh.w);
            }
            if (lcand) {
                uint4* rp = &S.g_row[(rb64 * 2 + (key == lk1 ? 0 : 1)) * 320 + cg * 40 + 2 * t];
#pragma unroll
                for (int j = 0; j < 10; ++j) st_ll16(rp + (j >> 1) * 8 + (j & 1), h2[2 * j], h2[2 * j + 1], ep);
#pragma unroll
                for (int j = 0; j < 10; ++j) st_ll16(rp + 160 + (j >> 1) * 8 + (j & 1), x1[2 * j], x1[2 * j + 1], ep);
            }
#pragma unroll
            for (int i = 0; i < 5; ++i) {
                const uint4 gb = *reinterpret_cast<const uint4*>(smem + OFF_TAB + 960 + i * 64 + t * 16);
                ov[4 * i] = hadd2_bf16(x1[4 * i], hmul2_bf16(gb.x, h2[4 * i]));
                ov[4 * i + 1] = hadd2_bf16(x1[4 * i + 1], hmul2_bf16(gb.y, h2[4 * i + 1]));
                ov[4 * i + 2] = hadd2_bf16(x1[4 * i + 2], hmul2_bf16(gb.z, h2[4 * i + 2]));
                ov[4 * i + 3] = hadd2_bf16(x1[4 * i + 3], hmul2_bf16(gb.w, h2[4 * i + 3]));
                if (!lcand) outp[4 * i] = make_uint4(ov[4 * i], ov[4 * i + 1], ov[4 * i + 2], ov[4 * i + 3]);
            }
        }
        TS(14);
        const uint32_t ldoff = (((lane >> 1) & 3) * 4 + (lane >> 4) * 2 + (lane & 1)) * 32 + ((((lane >> 3) ^ (lane >> 1)) & 1) << 4);
        uint32_t wa[12][4];
        if (bid < 96) {
            mbar_wait(BAR(B_GU), 0);
#pragma unroll
            for (int i = 0; i < 5; ++i) {
                ldmatrix4_t(wa[i], sb + OFF_GU + (warp * 5 + i) * 512 + ldoff);
                ldmatrix4_t(wa[5 + i], sb + OFF_GU + 20480 + (warp * 5 + i) * 512 + ldoff);
            }
        }
        mbar_wait(BAR(B_TOP), 0);
        TS(15);
        if (bid == 0 && tid == 0) S.g_epoch = ep;
        const uint2 top = *reinterpret_cast<const uint2*>(smem + OFF_CAND + 64);
        const int row0 = 2047 - (int)(top.x & 2047u), row1 = 2047 - (int)(top.y & 2047u);
        const int slot0 = (row0 >> 6) * 2, slot1 = (row1 >> 6) * 2 + ((row0 >> 6) == (row1 >> 6) ? 1 : 0);
        float* red = reinterpret_cast<float*>(smem + OFF_RED);
        if (bid < 96) {
            uint4 bf[5];
            const uint4* hp = &S.g_row[((g & 1) ? slot1 : slot0) * 320 + warp * 20 + t];
            uint32_t it = 0;
            bool ok;
            do {
                ok = true;
#pragma unroll
                for (int i = 0; i < 5; ++i) { bf[i] = ld_ll16(hp + 4 * i); ok = ok && bf[i].y == ep && bf[i].w == ep; }
            } while (!ok && ++it < SPIN_MAX);
            __syncwarp();
            float cgt[4] = {0.f, 0.f, 0.f, 0.f}, cup[4] = {0.f, 0.f, 0.f, 0.f};
#pragma unroll
            for (int i = 0; i < 5; ++i) { mma16816(cgt, wa[i], bf[i].x, bf[i].z); mma16816(cup, wa[5 + i], bf[i].x, bf[i].z); }
            float* rp = red + warp * 64 + (t & 1) * 16 + (t >> 1) * 8 + g;
            rp[0] = t == 0 ? cgt[0] : t == 1 ? cgt[1] : t == 2 ? cgt[2] : cgt[3];
            rp[32] = t == 0 ? cup[0] : t == 1 ? cup[1] : t == 2 ? cup[2] : cup[3];
            bar_sync(6, 256);
            if (warp == 0) {
                float gs = 0.f, us = 0.f;
#pragma unroll
                for (int i = 0; i < 8; ++i) { gs += red[i * 64 + lane]; us += red[i * 64 + 32 + lane]; }
                gs = rbf(gs); us = rbf(us);
                const float av = rbf(gs * sigmoidf_(gs)) * us;
                const float hi = __shfl_down_sync(~0u, av, 1);
                if (!(lane & 1)) st_ll8(reinterpret_cast<uint2*>(S.g_act) + bid * 16 + (lane >> 1), pack_bf16(av, hi), ep);
            }
        }
        TS(16);
        if (lcand && key != top.x && key != top.y) {
#pragma unroll
            for (int i = 0; i < 5; ++i) outp[4 * i] = make_uint4(ov[4 * i], ov[4 * i + 1], ov[4 * i + 2], ov[4 * i + 3]);
        }
        if (bid >= 88) {
            mbar_wait(BAR(B_DN), 0);
#pragma unroll
            for (int i = 0; i < 12; ++i) ldmatrix4_t(wa[i], sb + OFF_DN + (warp * 12 + i) * 512 + ldoff);
            uint2 fh, fx;
            uint32_t it = 0;
            {
                const uint2* fp = reinterpret_cast<const uint2*>(&S.g_row[((lane >> 4) ? slot1 : slot0) * 320]) + (bid - 88) * 8 + ((lane & 15) >> 1);
                do { fh = ld_ll8(fp); fx = ld_ll8(fp + 320); } while (!(fh.y == ep && fx.y == ep) && ++it < SPIN_MAX);
            }
            uint4 bf[12];
            const uint4* ap = &S.g_act[warp * 96 + (lane & 7)];
            bool ok;
            do {
                ok = true;
#pragma unroll
                for (int i = 0; i < 12; ++i) { bf[i] = ld_ll16(ap + 8 * i); ok = ok && bf[i].y == ep && bf[i].w == ep; }
                if (ACT_NS && !ok) __nanosleep(ACT_NS);
            } while (!ok && ++it < SPIN_MAX);
            __syncwarp();
            TS(17);
            float c0[4] = {0.f, 0.f, 0.f, 0.f}, c1[4] = {0.f, 0.f, 0.f, 0.f};
#pragma unroll
            for (int i = 0; i < 6; ++i) { mma16816(c0, wa[2 * i], bf[2 * i].x, bf[2 * i].z); mma16816(c1, wa[2 * i + 1], bf[2 * i + 1].x, bf[2 * i + 1].z); }
            float* rp = red + 512 + warp * 32 + (t & 1) * 16 + (t >> 1) * 8 + g;
            rp[0] = t == 0 ? c0[0] + c1[0] : t == 1 ? c0[1] + c1[1] : t == 2 ? c0[2] + c1[2] : c0[3] + c1[3];
            bar_sync(6, 256);
            if (warp == 0) {
                float y = 0.f;
#pragma unroll
                for (int i = 0; i < 8; ++i) y += red[512 + i * 32 + lane];
                const uint32_t ku = ((lane >> 4) ? top.y : top.x) & 0xFFFFF800u;
                const float r = rbf(__uint_as_float((ku & 0x80000000u) ? (ku & 0x7FFFFFFFu) | 0x400u : ~(ku | 0x400u)));
                const float y2 = rbf(rbf(y) * rbf(sigmoidf_(r)));
                const float h2 = (lane & 1) ? bf_hi(fh.x) : bf_lo(fh.x), xx = (lane & 1) ? bf_hi(fx.x) : bf_lo(fx.x);
                const float gbv = reinterpret_cast<const float*>(smem + OFF_GBD)[lane & 15];
                P.out[(size_t)((lane >> 4) ? row1 : row0) * DM + (bid - 88) * 16 + (lane & 15)] = __float2bfloat16_rn(xx + rbf(gbv * rbf(h2 + y2)));
            }
        }
        TS(18);
    }
}

}

typedef CUresult (*EncodeFn)(CUtensorMap*, CUtensorMapDataType, cuuint32_t, void*, const cuuint64_t*, const cuuint64_t*, const cuuint32_t*,
                             const cuuint32_t*, CUtensorMapInterleave, CUtensorMapSwizzle, CUtensorMapL2promotion, CUtensorMapFloatOOBfill);

extern "C" void kernel_launch(void* const* d_in, const int* in_sizes, int n_in, void* d_out, int out_size) {
    (void)in_sizes; (void)n_in; (void)out_size;
    static EncodeFn enc = nullptr;
    static void* scratch = nullptr;
    if (!enc) {
        void* fn = nullptr;
        cudaDriverEntryPointQueryResult qr;
        cudaGetDriverEntryPoint("cuTensorMapEncodeTiled", &fn, cudaEnableDefault, &qr);
        enc = (EncodeFn)fn;
        cudaGetSymbolAddress(&scratch, g_scratch);
        cudaFuncSetAttribute(fused_kernel, cudaFuncAttributeMaxDynamicSharedMemorySize, SMEM_BYTES);
    }
    Params P;
    P.x = (const __nv_bfloat16*)d_in[0];
    P.wqkv = (const __nv_bfloat16*)d_in[1];
    P.wo = (const __nv_bfloat16*)d_in[2];
    P.wr = (const __nv_bfloat16*)d_in[4];
    P.c = (const __nv_bfloat16*)d_in[8];
    P.wmod = (const __nv_bfloat16*)d_in[9];
    P.out = (__nv_bfloat16*)d_out;
    P.s = (Scratch*)scratch;
    P.zero = 0;
    Maps M;
    const cuuint32_t es[2] = {1, 1};
    auto mk = [&](CUtensorMap* m, void* p, cuuint64_t cols, cuuint64_t rows, cuuint32_t bc, cuuint32_t br, CUtensorMapSwizzle sw) {
        const cuuint64_t gd[2] = {cols, rows}, gs[1] = {cols * 2};
        const cuuint32_t bx[2] = {bc, br};
        enc(m, CU_TENSOR_MAP_DATA_TYPE_BFLOAT16, 2, p, gd, gs, bx, es, CU_TENSOR_MAP_INTERLEAVE_NONE, sw,
            CU_TENSOR_MAP_L2_PROMOTION_L2_256B, CU_TENSOR_MAP_FLOAT_OOB_FILL_NONE);
    };
    mk(&M.x, d_in[0], DM, SEQ, 64, 128, CU_TENSOR_MAP_SWIZZLE_128B);
    mk(&M.w[0], d_in[5], FF, DM, 16, 128, CU_TENSOR_MAP_SWIZZLE_32B);
    mk(&M.w[1], d_in[6], FF, DM, 16, 128, CU_TENSOR_MAP_SWIZZLE_32B);
    mk(&M.w[2], d_in[7], DM, FF, 16, 128, CU_TENSOR_MAP_SWIZZLE_32B);
    fused_kernel<<<NCTA, NTHR, SMEM_BYTES, cudaStreamPerThread>>>(P, M);
}
```
